```python
import torch

def _softmax(x, axis=-1):
    return torch.softmax(x, dim=axis)
def _gelu(x):
    return torch.nn.functional.gelu(x, approximate="tanh")
def _silu(x):
    return torch.nn.functional.silu(x)
def _sigmoid(x):
    return torch.sigmoid(x)
def _layernorm(x, axis=-1, eps=1e-5):
    m = x.mean(dim=axis, keepdim=True)
    v = x.var(dim=axis, keepdim=True, unbiased=False)
    return (x - m) / torch.sqrt(v + eps)
def _scatter_add(tgt, idx, src, axis=0):
    return tgt.clone().index_add_(axis, idx, src)
def _segment_sum(src, seg, n):
    out = torch.zeros((n,) + src.shape[1:], dtype=src.dtype)
    return out.index_add_(0, seg, src)
def _pad(x, pw):
    flat = tuple(v for pair in reversed(pw) for v in pair)
    return torch.nn.functional.pad(x, flat)

kernel_name = 'interleave_layers__mha_block__softmax_full_mha__prompt'

def setup_inputs():

    _w = (lambda a: (lambda t: t.to(torch.bfloat16) if t.is_floating_point() else t)(torch.as_tensor(a)))
    def _A_setup():
        B, S, D, H = 1, 2048, 448, 16
        return {
            "x": _w((lambda *s: torch.randn(*s, dtype=torch.bfloat16) * 0.05)(B, S, D)),
            "wqkv": _w((lambda *s: torch.randn(*s, dtype=torch.bfloat16) * 0.05)(D, 3 * D)),
            "wo": _w((lambda *s: torch.randn(*s, dtype=torch.bfloat16) * 0.05)(D, D)),
        }
    _A_in = _A_setup()

    def _B_setup():
        B, S, D = 1, 2048, 448
        return {
            "x": _w((lambda *s: torch.randn(*s, dtype=torch.bfloat16) * 0.05)(B, S, D)),
            "wqkv": _w((lambda *s: torch.randn(*s, dtype=torch.bfloat16) * 0.1)(D, 3 * D)),
            "wo": _w((lambda *s: torch.randn(*s, dtype=torch.bfloat16) * 0.05)(D, D)),
        }
    _B_in = _B_setup()

    return {
        "A_x": _A_in["x"],
        "A_wqkv": _A_in["wqkv"],
        "A_wo": _A_in["wo"],
        "B_x": _B_in["x"],
        "B_wqkv": _B_in["wqkv"],
        "B_wo": _B_in["wo"],
    }

def reference(A_x, A_wqkv, A_wo, B_x, B_wqkv, B_wo):
    def _A_ref(x, wqkv, wo):
        B, S, D = x.shape
        H = 16
        Dh = D // H
        qkv = (lambda x, *d: x.permute(*d))((x @ wqkv).reshape(B, S, 3, H, Dh), 2, 0, 3, 1, 4)
        q, k, v = qkv[0], qkv[1], qkv[2]
        scores = torch.einsum("bhqd,bhkd->bhqk", q, k) * (Dh ** -0.5)
        p = _softmax(scores, axis=-1)
        o = torch.einsum("bhqk,bhkd->bhqd", p, v)
        return (lambda x, *d: x.permute(*d))(o, 0, 2, 1, 3).reshape(B, S, D) @ wo

    def _B_ref(x, wqkv, wo):
        B, S, D = x.shape
        H = 16; Dh = D // H
        qkv = (lambda x, *d: x.permute(*d))((x @ wqkv).reshape(B, S, 3, H, Dh), 2, 0, 3, 1, 4)
        q, k, v = qkv[0], qkv[1], qkv[2]
        scale = Dh ** -0.5
        scores = torch.einsum("bhqd,bhkd->bhqk", q, k) * scale
        p = _softmax(scores, axis=-1)
        o = torch.einsum("bhqk,bhkd->bhqd", p, v)
        return (lambda x, *d: x.permute(*d))(o, 0, 2, 1, 3).reshape(B, S, D) @ wo

    x = A_x
    x = x + _A_ref(_layernorm(x, axis=-1), A_wqkv, A_wo)
    x = x + _B_ref(_layernorm(x, axis=-1), B_wqkv, B_wo)
    x = x + _A_ref(_layernorm(x, axis=-1), A_wqkv, A_wo)
    x = x + _B_ref(_layernorm(x, axis=-1), B_wqkv, B_wo)
    return x
```

```cpp
#include <cuda_runtime.h>
#include <cuda_bf16.h>
#include <stdint.h>

namespace mk {

constexpr int SEQ = 2048, DM = 448, NH = 16, NTILE = 32, NCTA = 128, NTHREADS = 640;

constexpr uint32_t SM_BASE = 1024;
constexpr uint32_t SLOT = 8192;
constexpr uint32_t W2_SBO = 1024, W2_CHUNK = 21 * W2_SBO;
constexpr uint32_t W2H = 8 * SLOT;
constexpr uint32_t W1R = W2H + 5 * W2_CHUNK;
constexpr uint32_t W1_SBO = 7168;
constexpr uint32_t BARS = W1R + 7 * W1_SBO;
constexpr uint32_t KMAX = BARS + 640;
constexpr uint32_t STATS = BARS + 768;
constexpr uint32_t SMEM_BYTES = STATS + 4096;
enum { B_FULLKV = 0, B_FULLKV0 = 4, B_FULLT = 8, B_W1RDY = 24, B_W2RDY = 25, B_W1FREE = 32, B_ZOK = 33, B_P2A = 34,
       B_EKV = 36, B_EP1 = 40  , B_EP2 = 48  , B_EKV0 = 56,
       B_TP = 60  , B_TKV0 = 76, B_COUNT = 80 };
__host__ __device__ constexpr uint32_t w2_chunk_off(int ch) { return ch < 5 ? W2H + ch * W2_CHUNK : W1R + (ch - 5) * W2_CHUNK; }

#define JM0_V 0xEE
#define JM1_V 0xEE
#define ATT_VAR 5
constexpr uint32_t JM0 = JM0_V, JM1 = JM1_V;

constexpr int ACT_TILE_BYTES = 64 * DM * 2;
__device__ uint4 g_y[2 * NTILE * ACT_TILE_BYTES / 16];
__device__ uint4 g_o[NTILE * ACT_TILE_BYTES / 16];
__device__ uint4 g_q[2 * NH * NTILE * 256];
__device__ uint4 g_kv[2 * NH * NTILE * 512];
__device__ __align__(16) float2 g_stats[2 * NTILE * 64 * 8];
__device__ unsigned long long g_kmax[2 * NH * 16];
constexpr int W2_IMG = 7 * W2_CHUNK, W1_IMG = 7 * W1_SBO;
__device__ uint4 g_w2[2 * 8 * W2_IMG / 16];
__device__ uint4 g_w1[2 * 8 * W1_IMG / 16];
__device__ unsigned g_flagW[2 * 8 * 32];
__device__ unsigned g_flagY[NTILE * 32], g_zcount;
__device__ __align__(128) unsigned g_flagQ[8 * 32];
__device__ unsigned g_epoch;

#define PROFP(idx)
#define PROFC(idx, cond)
#define NLAYERS 4

__device__ __forceinline__ void wg_fence() { asm volatile("wgmma.fence.sync.aligned;" ::: "memory"); }
__device__ __forceinline__ void wg_commit() { asm volatile("wgmma.commit_group.sync.aligned;" ::: "memory"); }
template <int N> __device__ __forceinline__ void wg_wait() { asm volatile("wgmma.wait_group.sync.aligned %0;" ::"n"(N) : "memory"); }
__host__ __device__ constexpr uint64_t mkdesc(uint32_t off, uint32_t lbo, uint32_t sbo) {
  return (uint64_t)(((SM_BASE + off) & 0x3FFFF) >> 4) | ((uint64_t)(lbo >> 4) << 16) | ((uint64_t)(sbo >> 4) << 32);
}
template <int N> __device__ __forceinline__ void fence_regs(float (&r)[N]) {
#pragma unroll
  for (int i = 0; i < N; i++) asm volatile("" : "+f"(r[i])::"memory");
}
template <int N> __device__ __forceinline__ void fence_regs(uint32_t (&r)[N]) {
#pragma unroll
  for (int i = 0; i < N; i++) asm volatile("" : "+r"(r[i])::"memory");
}
__device__ __forceinline__ void mbar_init(uint32_t bar, uint32_t cnt) { asm volatile("mbarrier.init.shared::cta.b64 [%0], %1;" ::"r"(bar), "r"(cnt) : "memory"); }
__device__ __forceinline__ void mbar_expect_tx(uint32_t bar, uint32_t bytes) {
  asm volatile("mbarrier.arrive.expect_tx.shared::cta.b64 _, [%0], %1;" ::"r"(bar), "r"(bytes) : "memory");
}
__device__ __forceinline__ void mbar_arrive(uint32_t bar) { asm volatile("mbarrier.arrive.shared::cta.b64 _, [%0];" ::"r"(bar) : "memory"); }
__device__ __forceinline__ void mbar_wait(uint32_t bar, uint32_t parity) {
  asm volatile(
      "{\n.reg .pred p;\n.reg .u32 c;\n"
      "mov.u32 c, 0;\n"
      "AGAIN:\n"
      "mbarrier.try_wait.parity.shared::cta.b64 p, [%0], %1;\n"
      "@p bra DONE;\n"
      "add.u32 c, c, 1;\n"
      "setp.lt.u32 p, c, 0x4000000;\n"
      "@p bra AGAIN;\n"
      "trap;\n"
      "DONE:\n}\n" ::"r"(bar), "r"(parity) : "memory");
}
__device__ __forceinline__ uint32_t mbar_test(uint32_t bar, uint32_t parity) {
  uint32_t ok;
  asm volatile("{\n.reg .pred p;\nmbarrier.test_wait.parity.shared::cta.b64 p, [%1], %2;\nselp.u32 %0, 1, 0, p;\n}\n" : "=r"(ok) : "r"(bar), "r"(parity) : "memory");
  return ok;
}
__device__ __forceinline__ void bulk_g2s(uint32_t dst, const void* src, uint32_t bytes, uint32_t bar) {
  asm volatile("cp.async.bulk.shared::cluster.global.mbarrier::complete_tx::bytes [%0], [%1], %2, [%3];" ::"r"(dst), "l"(src), "r"(bytes), "r"(bar) : "memory");
}
__device__ __forceinline__ void fence_proxy_async() { asm volatile("fence.proxy.async.global;" ::: "memory"); }
__device__ __forceinline__ unsigned ld_relaxed(const unsigned* p) {
  unsigned v;
  asm volatile("ld.relaxed.gpu.global.u32 %0, [%1];" : "=r"(v) : "l"(p) : "memory");
  return v;
}
__device__ __forceinline__ void fence_acquire() { asm volatile("fence.acquire.gpu;" ::: "memory"); }
__device__ __forceinline__ void red_release(unsigned* p) { asm volatile("red.release.gpu.global.add.u32 [%0], 1;" ::"l"(p) : "memory"); }
__device__ __forceinline__ void wait_flag(const unsigned* p, unsigned target) {
  uint32_t it = 0;
  while ((int)(ld_relaxed(p) - target) < 0)
    if (++it > (1u << 22)) __trap();
  fence_acquire();
}
__device__ __forceinline__ void wait_flag4(const unsigned* p, unsigned target) {
  uint32_t it = 0, a, b, c, d;
  do {
    asm volatile("ld.relaxed.gpu.global.v4.u32 {%0, %1, %2, %3}, [%4];" : "=r"(a), "=r"(b), "=r"(c), "=r"(d) : "l"(p) : "memory");
    if (++it > (1u << 22)) __trap();
  } while ((int)((a - target) | (b - target) | (c - target) | (d - target)) < 0);
  fence_acquire();
  fence_proxy_async();
}
template <int NT> __device__ __forceinline__ void hand_over(int barid) {
  fence_proxy_async();
  asm volatile("bar.arrive %0, %1;" ::"r"(barid), "n"(NT + 32) : "memory");
}
template <int NT> __device__ __forceinline__ void publish(int barid, unsigned* flag, int lane) {
  asm volatile("bar.sync %0, %1;" ::"r"(barid), "n"(NT + 32) : "memory");
  if (lane == 0) red_release(flag);
}
__device__ __forceinline__ uint32_t ldcg32(const void* p) {
  uint32_t v;
  asm volatile("ld.global.cg.u32 %0, [%1];" : "=r"(v) : "l"(p) : "memory");
  return v;
}
__device__ __forceinline__ uint32_t lds32(uint32_t a) {
  uint32_t v;
  asm volatile("ld.shared.u32 %0, [%1];" : "=r"(v) : "r"(a) : "memory");
  return v;
}
__device__ __forceinline__ float2 lds64f(uint32_t a) {
  float2 v;
  asm volatile("ld.shared.v2.f32 {%0, %1}, [%2];" : "=f"(v.x), "=f"(v.y) : "r"(a) : "memory");
  return v;
}
__device__ __forceinline__ void stg32(void* p, uint32_t v) { asm volatile("st.global.u32 [%0], %1;" ::"l"(p), "r"(v) : "memory"); }
__device__ __forceinline__ void st_word(void* p, uint32_t v) { asm volatile("st.relaxed.gpu.global.u32 [%0], %1;" ::"l"(p), "r"(max(v, 1u)) : "memory"); }
__device__ __forceinline__ uint4 ld_piece(const void* p) {
  uint4 v;
  asm volatile("ld.relaxed.gpu.global.v4.u32 {%0, %1, %2, %3}, [%4];" : "=r"(v.x), "=r"(v.y), "=r"(v.z), "=r"(v.w) : "l"(p) : "memory");
  return v;
}
__device__ __forceinline__ bool missing(const uint4& v) { return v.x == 0 || v.y == 0 || v.z == 0 || v.w == 0; }
__device__ __forceinline__ void sts128(uint32_t a, const uint4& v) {
  asm volatile("st.shared.v4.u32 [%0], {%1, %2, %3, %4};" ::"r"(a), "r"(v.x), "r"(v.y), "r"(v.z), "r"(v.w) : "memory");
}
__device__ __forceinline__ uint4 lds128(uint32_t a) {
  uint4 v;
  asm volatile("ld.shared.v4.u32 {%0, %1, %2, %3}, [%4];" : "=r"(v.x), "=r"(v.y), "=r"(v.z), "=r"(v.w) : "r"(a) : "memory");
  return v;
}
__device__ __forceinline__ uint4 repair(const void* src) {
  uint4 v;
  uint32_t it = 0;
  do {
    v = ld_piece(src);
    if (++it > (1u << 22)) __trap();
  } while (missing(v));
  return v;
}
__device__ __forceinline__ void wait_canary(const void* p, int delta) {
  uint32_t it = 0, a, b;
  do {
    a = ld_relaxed((const unsigned*)p);
    b = ld_relaxed((const unsigned*)((const unsigned char*)p + delta));
    if (++it > (1u << 22)) __trap();
  } while (a == 0 || b == 0);
  __syncwarp();
  fence_proxy_async();
}
__device__ __forceinline__ uint32_t pack_bf16(float lo, float hi) {
  uint32_t r;
  asm("cvt.rn.bf16x2.f32 %0, %1, %2;" : "=r"(r) : "f"(hi), "f"(lo));
  return r;
}
__device__ __forceinline__ float bf_lo(uint32_t v) { return __uint_as_float(v << 16); }
__device__ __forceinline__ float bf_hi(uint32_t v) { return __uint_as_float(v & 0xFFFF0000u); }
__device__ __forceinline__ float ex2(float x) {
  float e;
  asm("ex2.approx.ftz.f32 %0, %1;" : "=f"(e) : "f"(x));
  return e;
}
__device__ __forceinline__ float quad_sum(float v) {
  v += __shfl_xor_sync(0xffffffffu, v, 1);
  v += __shfl_xor_sync(0xffffffffu, v, 2);
  return v;
}

template <int ACC>
__device__ __forceinline__ void wgmma_qk(float (&d)[32], uint32_t a0, uint32_t a1, uint32_t a2, uint32_t a3, uint64_t descB) {
  asm volatile(
      "{\n.reg .pred p;\nsetp.ne.b32 p, %37, 0;\n"
      "wgmma.mma_async.sync.aligned.m64n64k16.f32.bf16.bf16 {"
      "%0, %1, %2, %3, %4, %5, %6, %7, %8, %9, %10, %11, %12, %13, %14, %15,"
      "%16, %17, %18, %19, %20, %21, %22, %23, %24, %25, %26, %27, %28, %29, %30, %31}, "
      "{%32, %33, %34, %35}, %36, p, 1, 1, 0;\n}\n"
      : "+f"(d[0]), "+f"(d[1]), "+f"(d[2]), "+f"(d[3]), "+f"(d[4]), "+f"(d[5]), "+f"(d[6]), "+f"(d[7]),
      "+f"(d[8]), "+f"(d[9]), "+f"(d[10]), "+f"(d[11]), "+f"(d[12]), "+f"(d[13]), "+f"(d[14]), "+f"(d[15]),
      "+f"(d[16]), "+f"(d[17]), "+f"(d[18]), "+f"(d[19]), "+f"(d[20]), "+f"(d[21]), "+f"(d[22]), "+f"(d[23]),
      "+f"(d[24]), "+f"(d[25]), "+f"(d[26]), "+f"(d[27]), "+f"(d[28]), "+f"(d[29]), "+f"(d[30]), "+f"(d[31])
      : "r"(a0), "r"(a1), "r"(a2), "r"(a3), "l"(descB), "n"(ACC));
}

template <int ACC>
__device__ __forceinline__ void wgmma_pv(float (&d)[16], uint32_t a0, uint32_t a1, uint32_t a2, uint32_t a3, uint64_t descB) {
  asm volatile(
      "{\n.reg .pred p;\nsetp.ne.b32 p, %21, 0;\n"
      "wgmma.mma_async.sync.aligned.m64n32k16.f32.bf16.bf16 {"
      "%0, %1, %2, %3, %4, %5, %6, %7, %8, %9, %10, %11, %12, %13, %14, %15}, "
      "{%16, %17, %18, %19}, %20, p, 1, 1, 1;\n}\n"
      : "+f"(d[0]), "+f"(d[1]), "+f"(d[2]), "+f"(d[3]), "+f"(d[4]), "+f"(d[5]), "+f"(d[6]), "+f"(d[7]),
      "+f"(d[8]), "+f"(d[9]), "+f"(d[10]), "+f"(d[11]), "+f"(d[12]), "+f"(d[13]), "+f"(d[14]), "+f"(d[15])
      : "r"(a0), "r"(a1), "r"(a2), "r"(a3), "l"(descB), "n"(ACC));
}

template <int ACC>
__device__ __forceinline__ void wgmma_p1(float (&d)[28], uint64_t descA, uint64_t descB) {
  asm volatile(
      "{\n.reg .pred p;\nsetp.ne.b32 p, %30, 0;\n"
      "wgmma.mma_async.sync.aligned.m64n56k16.f32.bf16.bf16 {"
      "%0, %1, %2, %3, %4, %5, %6, %7, %8, %9, %10, %11, %12, %13, %14, %15,"
      "%16, %17, %18, %19, %20, %21, %22, %23, %24, %25, %26, %27}, "
      "%28, %29, p, 1, 1, 0, 1;\n}\n"
      : "+f"(d[0]), "+f"(d[1]), "+f"(d[2]), "+f"(d[3]), "+f"(d[4]), "+f"(d[5]), "+f"(d[6]), "+f"(d[7]),
      "+f"(d[8]), "+f"(d[9]), "+f"(d[10]), "+f"(d[11]), "+f"(d[12]), "+f"(d[13]), "+f"(d[14]), "+f"(d[15]),
      "+f"(d[16]), "+f"(d[17]), "+f"(d[18]), "+f"(d[19]), "+f"(d[20]), "+f"(d[21]), "+f"(d[22]), "+f"(d[23]),
      "+f"(d[24]), "+f"(d[25]), "+f"(d[26]), "+f"(d[27])
      : "l"(descA), "l"(descB), "n"(ACC));
}

template <int ACC>
__device__ __forceinline__ void wgmma_p2(float (&d)[44], uint32_t a0, uint32_t a1, uint32_t a2, uint32_t a3, uint64_t descB) {
  asm volatile(
      "{\n.reg .pred p;\nsetp.ne.b32 p, %49, 0;\n"
      "wgmma.mma_async.sync.aligned.m64n88k16.f32.bf16.bf16 {"
      "%0, %1, %2, %3, %4, %5, %6, %7, %8, %9, %10, %11, %12, %13, %14, %15,"
      "%16, %17, %18, %19, %20, %21, %22, %23, %24, %25, %26, %27, %28, %29, %30, %31,"
      "%32, %33, %34, %35, %36, %37, %38, %39, %40, %41, %42, %43}, "
      "{%44, %45, %46, %47}, %48, p, 1, 1, 1;\n}\n"
      : "+f"(d[0]), "+f"(d[1]), "+f"(d[2]), "+f"(d[3]), "+f"(d[4]), "+f"(d[5]), "+f"(d[6]), "+f"(d[7]),
      "+f"(d[8]), "+f"(d[9]), "+f"(d[10]), "+f"(d[11]), "+f"(d[12]), "+f"(d[13]), "+f"(d[14]), "+f"(d[15]),
      "+f"(d[16]), "+f"(d[17]), "+f"(d[18]), "+f"(d[19]), "+f"(d[20]), "+f"(d[21]), "+f"(d[22]), "+f"(d[23]),
      "+f"(d[24]), "+f"(d[25]), "+f"(d[26]), "+f"(d[27]), "+f"(d[28]), "+f"(d[29]), "+f"(d[30]), "+f"(d[31]),
      "+f"(d[32]), "+f"(d[33]), "+f"(d[34]), "+f"(d[35]), "+f"(d[36]), "+f"(d[37]), "+f"(d[38]), "+f"(d[39]),
      "+f"(d[40]), "+f"(d[41]), "+f"(d[42]), "+f"(d[43])
      : "r"(a0), "r"(a1), "r"(a2), "r"(a3), "l"(descB), "n"(ACC));
}

__device__ __forceinline__ uint32_t exp_mufu(float x0, float x1) { return pack_bf16(ex2(x0), ex2(x1)); }
__device__ __forceinline__ uint32_t exp_poly(float x0, float x1, uint32_t c2) {
  uint32_t t0 = __float_as_uint(x0), t1 = __float_as_uint(x1), u, n, h, r;
  asm("prmt.b32 %0, %1, %2, 0xF5B1;" : "=r"(u) : "r"(t0), "r"(t1));
  asm("prmt.b32 %0, %1, %2, 0xF6B2;" : "=r"(n) : "r"(t0), "r"(t1));
  asm("fma.rn.f16x2 %0, %1, %2, %3;" : "=r"(h) : "r"(c2), "r"(u), "r"(0x353C353Cu));
  asm("fma.rn.f16x2 %0, %1, %2, %3;" : "=r"(h) : "r"(h), "r"(u), "r"(0x04000400u));
  asm("mad.lo.u32 %0, %1, 128, %2;" : "=r"(r) : "r"(n), "r"(h));
  return r;
}
template <uint32_t JM, int LO, int HI> __device__ __forceinline__ void softmax_tile(const float (&s)[32], uint32_t (&p)[16], uint32_t c2) {
#pragma unroll
  for (int i = LO; i < HI; i++) p[i] = ((JM >> (i >> 1)) & 1) ? exp_poly(s[2 * i], s[2 * i + 1], c2) : exp_mufu(s[2 * i], s[2 * i + 1]);
}
template <int SL> __device__ __forceinline__ void issue_qk(float (&s)[32], const uint32_t (&q)[8]) {
  wgmma_qk<0>(s, q[0], q[1], q[2], q[3], mkdesc(SL * SLOT, 128, 512));
  wgmma_qk<1>(s, q[4], q[5], q[6], q[7], mkdesc(SL * SLOT + 256, 128, 512));
}
template <int SL> __device__ __forceinline__ void issue_pv(float (&o)[16], uint32_t (&p)[16]) {
  fence_regs(p);
  wg_fence();
#pragma unroll
  for (int j = 0; j < 4; j++) wgmma_pv<1>(o, p[4 * j], p[4 * j + 1], p[4 * j + 2], p[4 * j + 3], mkdesc(SL * SLOT + 4096 + j * 1024, 512, 128));
  wg_commit();
}
template <int I>
__device__ __forceinline__ void att_step(float (&s)[32], float (&o)[16], const uint32_t (&q)[8], uint32_t (&p)[16], uint32_t ecur, uint32_t par,
                                         uint32_t c2, int lane, uint32_t& rdy) {
  constexpr int KS = (I + 1) & 7;
  constexpr uint32_t bars = SM_BASE + BARS;
  issue_pv<I>(o, p);
  if ((I & 1) && !rdy) mbar_wait(bars + (B_FULLKV + KS / 2) * 8, I == 7 ? par ^ 1 : par);
  wg_wait<0>();
  fence_regs(o);
  wg_fence();
  issue_qk<KS>(s, q);
  wg_commit();
  if ((I & 1) && lane == 0) mbar_arrive(ecur + (I / 2) * 8);
  if (!(I & 1)) rdy = mbar_test(bars + (B_FULLKV + ((I + 2) & 7) / 2) * 8, I == 6 ? par ^ 1 : par);
  wg_wait<0>();
  fence_regs(s);
  softmax_tile<(KS & 1) ? JM1 : JM0, 0, 16>(s, p, c2);
}

__device__ __forceinline__ void mma16816(float (&d)[4], uint32_t a0, uint32_t a1, uint32_t a2, uint32_t a3, uint32_t b0, uint32_t b1) {
  asm volatile("mma.sync.aligned.m16n8k16.row.col.f32.bf16.bf16.f32 {%0,%1,%2,%3}, {%4,%5,%6,%7}, {%8,%9}, {%0,%1,%2,%3};"
               : "+f"(d[0]), "+f"(d[1]), "+f"(d[2]), "+f"(d[3])
               : "r"(a0), "r"(a1), "r"(a2), "r"(a3), "r"(b0), "r"(b1));
}
__device__ __forceinline__ void attend_safe(float* o_out, const uint32_t* q_in, const unsigned char* kv, int lane) {
  uint32_t q[8];
#pragma unroll
  for (int i = 0; i < 8; i++) q[i] = q_in[i];
  float o[4][4];
#pragma unroll
  for (int i = 0; i < 16; i++) o[i >> 2][i & 3] = 0.f;
  float m0 = -INFINITY, m1 = -INFINITY;
  const int c = lane & 3, r = lane >> 2;
#pragma unroll 1
  for (int blk = 0; blk < SEQ / 16; blk++) {
    const unsigned char* kb = kv + (size_t)(blk >> 2) * 8192 + (blk & 3) * 1024;
    float s[2][4];
#pragma unroll
    for (int n = 0; n < 2; n++) {
#pragma unroll
      for (int i = 0; i < 4; i++) s[n][i] = 0.f;
      const unsigned char* kp = kb + n * 512 + lane * 4;
      mma16816(s[n], q[0], q[1], q[2], q[3], ldcg32(kp), ldcg32(kp + 128));
      mma16816(s[n], q[4], q[5], q[6], q[7], ldcg32(kp + 256), ldcg32(kp + 384));
    }
    float t0 = fmaxf(fmaxf(s[0][0], s[0][1]), fmaxf(s[1][0], s[1][1]));
    float t1 = fmaxf(fmaxf(s[0][2], s[0][3]), fmaxf(s[1][2], s[1][3]));
    t0 = fmaxf(t0, __shfl_xor_sync(0xffffffffu, t0, 1)); t0 = fmaxf(t0, __shfl_xor_sync(0xffffffffu, t0, 2));
    t1 = fmaxf(t1, __shfl_xor_sync(0xffffffffu, t1, 1)); t1 = fmaxf(t1, __shfl_xor_sync(0xffffffffu, t1, 2));
    const float n0 = fmaxf(m0, t0), n1 = fmaxf(m1, t1);
    const float f0 = ex2(m0 - n0), f1 = ex2(m1 - n1);
    m0 = n0; m1 = n1;
    const uint32_t a0 = pack_bf16(ex2(s[0][0] - n0), ex2(s[0][1] - n0)), a1 = pack_bf16(ex2(s[0][2] - n1), ex2(s[0][3] - n1));
    const uint32_t a2 = pack_bf16(ex2(s[1][0] - n0), ex2(s[1][1] - n0)), a3 = pack_bf16(ex2(s[1][2] - n1), ex2(s[1][3] - n1));
#pragma unroll
    for (int dg = 0; dg < 4; dg++) {
      o[dg][0] *= f0; o[dg][1] *= f0; o[dg][2] *= f1; o[dg][3] *= f1;
      const unsigned char* vp = kb + 4096 + dg * 128 + c * 32 + (r >> 1) * 4;
      const uint32_t sel = (r & 1) ? 0x7632 : 0x5410;
      const uint32_t b0 = __byte_perm(ldcg32(vp), ldcg32(vp + 16), sel);
      const uint32_t b1 = __byte_perm(ldcg32(vp + 512), ldcg32(vp + 528), sel);
      mma16816(o[dg], a0, a1, a2, a3, b0, b1);
    }
  }
#pragma unroll
  for (int i = 0; i < 16; i++) o_out[i] = o[i >> 2][i & 3];
}

__device__ __forceinline__ void attention(int layer, int h, int rt, int wg, unsigned ep4, uint32_t sb, int warp, int lane) {
  const uint32_t bars = sb + BARS;
  const int par = layer & 1;
  if (layer == 0) {
    if (lane == 0) wait_flag(&g_flagQ[(h >> 1) * 32 + rt], ep4 + 1);
    __syncwarp();
  }
  uint32_t q[8];
  const unsigned char* qp = (const unsigned char*)g_q + ((size_t)(par * NH + h) * NTILE + rt) * 4096 + warp * 1024 + lane * 4;
  {
    uint32_t it = 0;
    while (ld_relaxed((const unsigned*)(qp + 512 + 384)) == 0)
      if (++it > (1u << 22)) __trap();
    do {
#pragma unroll
      for (int i = 0; i < 8; i++) q[i] = ld_relaxed((const unsigned*)(qp + (i & 1) * 512 + (i >> 1) * 128));
      if (++it > (1u << 22)) __trap();
    } while (q[0] == 0 || q[1] == 0 || q[2] == 0 || q[3] == 0 || q[4] == 0 || q[5] == 0 || q[6] == 0 || q[7] == 0);
    __syncwarp();
  }
  PROFP(layer * 12 + 4);
  uint32_t c2 = 0x71627162u;
  asm volatile("" : "+r"(c2));
  float s[32], o[16];
  uint32_t p[16];
#pragma unroll
  for (int i = 0; i < 16; i++) o[i] = 0.f;
  fence_regs(o);
  mbar_wait(bars + B_FULLKV * 8, 0);
  PROFP(layer * 12 + 5);
  PROFC(55, layer == 2);
  wg_fence();
  issue_qk<0>(s, q);
  wg_commit();
  wg_wait<0>();
  fence_regs(s);
  softmax_tile<JM0, 0, 16>(s, p, c2);
  uint32_t rdy = 0;
#pragma unroll 1
  for (int R = 0; R < 4; R++) {
    const uint32_t pr = R & 1, ecur = bars + (R == 3 ? B_EP1 : B_EKV) * 8;
    att_step<0>(s, o, q, p, ecur, pr, c2, lane, rdy);
    att_step<1>(s, o, q, p, ecur, pr, c2, lane, rdy);
    att_step<2>(s, o, q, p, ecur, pr, c2, lane, rdy);
    att_step<3>(s, o, q, p, ecur, pr, c2, lane, rdy);
    att_step<4>(s, o, q, p, ecur, pr, c2, lane, rdy);
    att_step<5>(s, o, q, p, ecur, pr, c2, lane, rdy);
    att_step<6>(s, o, q, p, ecur, pr, c2, lane, rdy);
    if (R == 3) break;
    att_step<7>(s, o, q, p, ecur, pr, c2, lane, rdy);
  }
  PROFP(layer * 12 + 6);
  PROFC(56, layer == 2);
  issue_pv<7>(o, p);
  const int c = lane & 3, odd = h & 1;
  const bool padlane = odd ? (c < 2) : (c >= 2);
  if (padlane) { q[6] = 0; q[7] = 0; }
  float qa = 0.f, qb = 0.f;
#pragma unroll
  for (int i = 0; i < 8; i += 2) {
    qa += bf_lo(q[i]) * bf_lo(q[i]) + bf_hi(q[i]) * bf_hi(q[i]);
    qb += bf_lo(q[i + 1]) * bf_lo(q[i + 1]) + bf_hi(q[i + 1]) * bf_hi(q[i + 1]);
  }
  qa = quad_sum(qa); qb = quad_sum(qb);
  const float km = __uint_as_float(lds32(sb + KMAX + par * 4));
  wg_wait<0>();
  fence_regs(o);
  if (lane == 0) mbar_arrive(bars + (B_EP1 + 3) * 8);
  const int lsrc = (lane & ~3) | (odd ? 0 : 2);
  float la = __shfl_sync(0xffffffffu, o[12], lsrc), lb = __shfl_sync(0xffffffffu, o[14], lsrc);
  const float lo_lim = 7.8886e-31f  , hi_lim = 512.f;
  const bool ok = (fmaxf(qa, qb) * km <= 124.f * 124.f) && la >= lo_lim && la < hi_lim && lb >= lo_lim && lb < hi_lim;
  if (!__all_sync(0xffffffffu, ok)) {
    float ot[16];
    attend_safe(ot, q, (const unsigned char*)g_kv + (size_t)(par * NH + h) * NTILE * 8192, lane);
#pragma unroll
    for (int i = 0; i < 16; i++) o[i] = ot[i];
    la = __shfl_sync(0xffffffffu, o[12], lsrc);
    lb = __shfl_sync(0xffffffffu, o[14], lsrc);
  }
  const float ia = 1.f / la, ib = 1.f / lb;
  mbar_wait(bars + B_ZOK * 8, par);
  unsigned char* op = (unsigned char*)g_o + (size_t)rt * ACT_TILE_BYTES + (7 * (h >> 1)) * 1024 + warp * 256 + lane * 4;
#pragma unroll
  for (int j = 0; j < 3; j++) {
    st_word(op + (j + 4 * odd) * 1024, pack_bf16(o[4 * j] * ia, o[4 * j + 1] * ia));
    st_word(op + (j + 4 * odd) * 1024 + 128, pack_bf16(o[4 * j + 2] * ib, o[4 * j + 3] * ib));
  }
  if (!padlane) {
    st_word(op + 3 * 1024, pack_bf16(o[12] * ia, o[13] * ia));
    st_word(op + 3 * 1024 + 128, pack_bf16(o[14] * ib, o[15] * ib));
  }
  PROFP(layer * 12 + 7);
}

__device__ __forceinline__ void store_y(const uint32_t (&yv)[14], int par, int rt, int cs, int warp, int lane) {
  unsigned char* yp = (unsigned char*)g_y + (size_t)(par * NTILE + rt) * ACT_TILE_BYTES + (7 * cs) * 1024 + warp * 256 + lane * 4;
  float sa = 0.f, sb = 0.f;
#pragma unroll
  for (int j = 0; j < 7; j++) {
    st_word(yp + j * 1024, yv[2 * j]);
    st_word(yp + j * 1024 + 128, yv[2 * j + 1]);
    sa += bf_lo(yv[2 * j]) + bf_hi(yv[2 * j]);
    sb += bf_lo(yv[2 * j + 1]) + bf_hi(yv[2 * j + 1]);
  }
  sa = quad_sum(sa) * (1.f / 56.f);
  sb = quad_sum(sb) * (1.f / 56.f);
  float va = 0.f, vb = 0.f;
#pragma unroll
  for (int j = 0; j < 7; j++) {
    float d;
    d = bf_lo(yv[2 * j]) - sa; va += d * d;
    d = bf_hi(yv[2 * j]) - sa; va += d * d;
    d = bf_lo(yv[2 * j + 1]) - sb; vb += d * d;
    d = bf_hi(yv[2 * j + 1]) - sb; vb += d * d;
  }
  va = quad_sum(va);
  vb = quad_sum(vb);
  const int c = lane & 3;
  st_word((unsigned*)(g_stats + ((par * NTILE + rt) * 64 + warp * 16 + (lane >> 2) + (c >> 1) * 8) * 8 + cs) + (c & 1),
          __float_as_uint(c == 0 ? sa : c == 1 ? va : c == 2 ? sb : vb));
}

__device__ __forceinline__ uint32_t sub_bf16x2(uint32_t a, uint32_t b) {
  uint32_t r;
  asm("sub.rn.bf16x2 %0, %1, %2;" : "=r"(r) : "r"(a), "r"(b));
  return r;
}
template <int NK> __device__ __forceinline__ void load_frags(uint32_t (&x)[NK][4], uint32_t addr) {
#pragma unroll
  for (int i = 0; i < NK; i++)
    asm volatile("ldmatrix.sync.aligned.m8n8.x4.shared.b16 {%0,%1,%2,%3}, [%4];"
                 : "=r"(x[i][0]), "=r"(x[i][1]), "=r"(x[i][2]), "=r"(x[i][3]) : "r"(addr + i * 2048) : "memory");
}
template <int NK> __device__ __forceinline__ uint32_t min_frags(uint32_t m, const uint32_t (&x)[NK][4]) {
#pragma unroll
  for (int i = 0; i < NK; i++) m = min(min(m, min(x[i][0], x[i][1])), min(x[i][2], x[i][3]));
  return m;
}
template <int NG, bool W2>
__device__ __forceinline__ void redo_rows(float (&acc)[4 * NG], const unsigned char* gsrc, uint32_t m0, uint32_t m1, uint32_t woff, int lane) {
#pragma unroll
  for (int i = 0; i < 4 * NG; i++) acc[i] = 0.f;
#pragma unroll 1
  for (int ks = 0; ks < 28; ks++) {
    uint32_t x[4], it = 0;
    do {
#pragma unroll
      for (int i = 0; i < 4; i++) x[i] = ld_relaxed((const unsigned*)(gsrc + ks * 2048 + (i >> 1) * 1024 + (i & 1) * 128));
      if (++it > (1u << 22)) __trap();
    } while (x[0] == 0 || x[1] == 0 || x[2] == 0 || x[3] == 0);
    __syncwarp();
    x[0] = sub_bf16x2(x[0], m0); x[1] = sub_bf16x2(x[1], m1); x[2] = sub_bf16x2(x[2], m0); x[3] = sub_bf16x2(x[3], m1);
    const uint32_t wa = SM_BASE + woff + (W2 ? w2_chunk_off(ks >> 2) + (ks & 3) * 256 : W1R + ks * 256) + (lane & 15) * 16;
#pragma unroll
    for (int j = 0; j < NG; j++) {
      uint32_t b0, b1;
      asm volatile("ldmatrix.sync.aligned.m8n8.x2.trans.shared.b16 {%0,%1}, [%2];" : "=r"(b0), "=r"(b1) : "r"(wa + j * (W2 ? W2_SBO : W1_SBO)) : "memory");
      float d[4] = {acc[4 * j], acc[4 * j + 1], acc[4 * j + 2], acc[4 * j + 3]};
      mma16816(d, x[0], x[1], x[2], x[3], b0, b1);
      acc[4 * j] = d[0]; acc[4 * j + 1] = d[1]; acc[4 * j + 2] = d[2]; acc[4 * j + 3] = d[3];
    }
  }
}
#define NEED_REDO(chk) __any_sync(0xffffffffu, (chk) == 0)

__device__ __forceinline__ void proj_out(int layer, int rt, int cs, int half, __nv_bfloat16* out, uint32_t sb, int warp, int lane) {
  const uint32_t bars = sb + BARS, tbar = bars + (B_TP + half * 4) * 8, par = layer & 1;
  const uint32_t erel = bars + (half == 0 ? B_EP1 + 4 : B_EP2) * 8;
  const unsigned char* gsrc = (const unsigned char*)g_o + (size_t)rt * ACT_TILE_BYTES + warp * 256 + lane * 4;
  const uint32_t la = sb + (lane >> 4) * 1024 + (warp * 2 + ((lane >> 3) & 1)) * 128 + (lane & 7) * 16;
  uint32_t xr[14];
  {
    const unsigned char* yp = (const unsigned char*)g_y + (size_t)(par * NTILE + rt) * ACT_TILE_BYTES + (7 * cs) * 1024 + warp * 256 + lane * 4;
#pragma unroll
    for (int i = 0; i < 14; i++) xr[i] = ld_relaxed((const unsigned*)(yp + (i >> 1) * 1024 + (i & 1) * 128));
  }
  float acc[28];
  uint32_t chk = 0xffffffffu, trdy = 0;
  mbar_wait(bars + B_W1RDY * 8, par);
#define OUT_MMA(ST)                                                                                   \
  if (!trdy) mbar_wait(tbar + ST * 8, par);                                                           \
  wg_fence();                                                                                         \
  _Pragma("unroll") for (int ks = 8 * ST; ks < (ST == 3 ? 28 : 8 * ST + 8); ks++) {                   \
    const uint64_t da = mkdesc(ks * 2048, 1024, 128), db = mkdesc(W1R + ks * 256, 128, W1_SBO);       \
    if (ks == 0) wgmma_p1<0>(acc, da, db); else wgmma_p1<1>(acc, da, db);                             \
  }                                                                                                   \
  wg_commit();                                                                                        \
  if (ST < 3) trdy = mbar_test(tbar + (ST + 1) * 8, par);                                             \
  _Pragma("unroll") for (int e = 0; e < (ST == 3 ? 1 : 2); e++) {                                     \
    uint32_t x[4][4];                                                                                 \
    load_frags<4>(x, la + (2 * ST + e) * SLOT);                                                       \
    chk = min_frags<4>(chk, x);                                                                       \
  }                                                                                                   \
  if (ST > 0) {                                                                                       \
    wg_wait<1>();                                                                                     \
    if (lane == 0) mbar_arrive(erel + (ST > 0 ? ST - 1 : 0) * 8);                                     \
  }
  OUT_MMA(0) OUT_MMA(1) OUT_MMA(2) OUT_MMA(3)
#undef OUT_MMA
  wg_wait<0>();
  fence_regs(acc);
  if (lane == 0) mbar_arrive(erel + 24);
  if (NEED_REDO(chk)) redo_rows<7, false>(acc, gsrc, 0u, 0u, 0, lane);
  __syncwarp();
  PROFP(layer * 12 + 9);
  if (lane == 0) mbar_arrive(bars + B_W1FREE * 8);
  uint32_t yv[14];
#pragma unroll
  for (int i = 0; i < 14; i++) {
    const uint32_t a = pack_bf16(acc[2 * i], acc[2 * i + 1]);
    yv[i] = pack_bf16(bf_lo(xr[i]) + bf_lo(a), bf_hi(xr[i]) + bf_hi(a));
  }
  if (layer < NLAYERS - 1) {
    store_y(yv, par ^ 1, rt, cs, warp, lane);
  } else {
    __nv_bfloat16* op = out + (size_t)(rt * 64 + warp * 16 + (lane >> 2)) * DM + cs * 56 + (lane & 3) * 2;
#pragma unroll
    for (int j = 0; j < 7; j++) {
      stg32(op + j * 8, yv[2 * j]);
      stg32(op + 8 * DM + j * 8, yv[2 * j + 1]);
    }
  }
}

__device__ __forceinline__ void qkv_main(float (&acc)[44], float (&rs)[2], int part, int nl, int rt, int half, uint32_t sb, int warp, int lane) {
  const uint32_t bars = sb + BARS, tbar = bars + (B_TP + (2 + half) * 4) * 8, par = nl & 1;
  const uint32_t erel = bars + (half == 0 ? B_EP2 + 4 : B_EKV0) * 8;
  const int c = lane & 3;
  const unsigned char* gsrc = (const unsigned char*)g_y + (size_t)(par * NTILE + rt) * ACT_TILE_BYTES + warp * 256 + lane * 4;
  const uint32_t la = sb + (lane >> 4) * 1024 + (warp * 2 + ((lane >> 3) & 1)) * 128 + (lane & 7) * 16;
  PROFP(nl * 12 + 0);
  mbar_wait(bars + B_W2RDY * 8, par);
  mbar_wait(tbar, par);
  PROFP(nl * 12 + 1);
  uint32_t x[2][4], a[2][2][4];
  load_frags<2>(x, la);
  uint32_t m2[2];
#pragma unroll
  for (int hh = 0; hh < 2; hh++) {
    const int row = warp * 16 + (lane >> 2) + 8 * hh;
    uint4 sv = lds128(sb + STATS + row * 64 + c * 16);
    if (missing(sv)) sv = repair((const unsigned char*)(g_stats + ((par * NTILE + rt) * 64 + row) * 8) + c * 16);
    __syncwarp();
    const float mean = quad_sum(__uint_as_float(sv.x) + __uint_as_float(sv.z)) * 0.125f;
    const float d0 = __uint_as_float(sv.x) - mean, d1 = __uint_as_float(sv.z) - mean;
    const float var = quad_sum(__uint_as_float(sv.y) + __uint_as_float(sv.w) + 56.f * (d0 * d0 + d1 * d1));
    rs[hh] = rsqrtf(var * (1.f / DM) + 1e-5f);
    m2[hh] = pack_bf16(mean, mean);
  }
  uint32_t chk = 0xffffffffu, trdy = 0, wrdy = 0;
  const uint64_t dpart = part * (10 * W2_SBO >> 4);
#pragma unroll
  for (int g = 0; g < 14; g++) {
    chk = min_frags<2>(chk, x);
    if ((g & 1) == 0 && g > 0 && !wrdy) mbar_wait(bars + (B_W2RDY + (g >> 1)) * 8, par);
    if (g >= 2) wg_wait<1>();
#pragma unroll
    for (int i = 0; i < 8; i++) a[g & 1][i >> 2][i & 3] = sub_bf16x2(x[i >> 2][i & 3], m2[i & 1]);
    fence_regs(a[g & 1][0]);
    fence_regs(a[g & 1][1]);
    wg_fence();
#pragma unroll
    for (int i = 0; i < 2; i++) {
      const uint64_t db = mkdesc(w2_chunk_off(g >> 1) + ((g & 1) * 2 + i) * 256, 128, W2_SBO) + dpart;
      const uint32_t(&f)[4] = a[g & 1][i];
      if (g == 0 && i == 0) wgmma_p2<0>(acc, f[0], f[1], f[2], f[3], db); else wgmma_p2<1>(acc, f[0], f[1], f[2], f[3], db);
    }
    wg_commit();
    if (((g & 3) == 3 || g == 13) && lane == 0) mbar_arrive(erel + (g >> 2) * 8);
    if (g < 13) {
      if ((g & 3) == 3 && !trdy) mbar_wait(tbar + ((g + 1) >> 2) * 8, par);
      load_frags<2>(x, la + (g + 1) * 4096);
      if ((g & 3) == 1) trdy = mbar_test(tbar + ((g + 3) >> 2) * 8, par);
      if ((g & 1) == 0 && g < 12) wrdy = mbar_test(bars + (B_W2RDY + (g >> 1) + 1) * 8, par);
    }
  }
  wg_wait<0>();
  fence_regs(acc);
  if (NEED_REDO(chk)) redo_rows<11, true>(acc, gsrc, m2[0], m2[1], part * 10 * W2_SBO, lane);
  PROFP(nl * 12 + 2);
}
template <int PART>
__device__ __forceinline__ void qkv_store(const float (&acc)[44], const float (&rs)[2], int nl, unsigned ep4, int rt, int cs, int half, int warp, int lane) {
  const int par = nl & 1, c = lane & 3;
  const float qs = 0.18898223650461362f * 1.4426950408889634f;
  const size_t hb = (size_t)(par * NH + 2 * cs) * NTILE + rt;
  unsigned char* fp = (PART == 0 ? (unsigned char*)g_q + hb * 4096 : (unsigned char*)g_kv + hb * 8192 + 4096) + warp * 1024 + lane * 4;
  constexpr size_t hstride = (size_t)NTILE * (PART == 0 ? 4096 : 8192);
  unsigned char* kp = (unsigned char*)g_kv + (hb + PART * NTILE) * 8192 + warp * 1024 + lane * 4;
  const uint32_t jm = (rt & 1) ? JM1 : JM0;
  const bool lo2 = c < 2, first = (c & 1) == 0;
  float nk[2] = {0.f, 0.f};
#pragma unroll
  for (int hh = 0; hh < 2; hh++) {
    const bool poly = (jm >> (warp * 2 + hh)) & 1;
    const uint32_t kpad = first ? (poly ? 0x00003F80u : 0x3F800000u) : (poly ? 0x00003F80u : 0x8000u);
#pragma unroll
    for (int j = 0; j < 4; j++) {
      const int jl = PART == 0 ? 7 + j : (j + 1) & 3;
      const float v0 = acc[4 * jl + 2 * hh] * rs[hh], v1 = acc[4 * jl + 2 * hh + 1] * rs[hh];
      const bool real = j < 3 || (PART == 0 ? lo2 : !lo2);
      nk[hh] += real ? v0 * v0 + v1 * v1 : 0.f;
      st_word(kp + hh * 512 + j * 128, real ? pack_bf16(v0, v1) : kpad);
    }
  }
#pragma unroll
  for (int hh = 0; hh < 2; hh++) {
    const float sc = PART == 0 ? rs[hh] * qs : rs[hh];
    const uint32_t pad = PART == 0 ? (first ? 0xC25C4340u   : 0x00003BAFu  ) : (first ? 0x00003F80u : 0x8000u);
#pragma unroll
    for (int jj = 0; jj < 7; jj++) {
      const int jl = PART == 0 ? jj : 4 + jj;
      const uint32_t v = pack_bf16(acc[4 * jl + 2 * hh] * sc, acc[4 * jl + 2 * hh + 1] * sc);
      if (jj < 3) st_word(fp + hh * 512 + jj * 128, v);
      else if (jj > 3) st_word(fp + hstride + hh * 512 + (jj - 4) * 128, v);
      else {
        st_word(fp + hh * 512 + 384, lo2 ? v : pad);
        st_word(fp + hstride + hh * 512 + 384, lo2 ? pad : v);
      }
    }
  }
  float km = fmaxf(quad_sum(nk[0]), quad_sum(nk[1]));
#pragma unroll
  for (int d = 4; d < 32; d <<= 1) km = fmaxf(km, __shfl_xor_sync(0xffffffffu, km, d));
  if (lane == 0) atomicMax(&g_kmax[(par * NH + 2 * cs + PART) * 16], ((unsigned long long)(ep4 + nl + 1) << 32) | __float_as_uint(km));
  hand_over<256>(5 + half);
  PROFP(nl * 12 + 3);
}

__device__ __forceinline__ void tile_w2(const __nv_bfloat16* w, int set, int kb, int cs, int t) {
#pragma unroll
  for (int i = 0; i < 3; i++) {
    const int idx = t + i * 256;
    if (idx < 588) {
      const int k = kb * 28 + idx / 21, g = idx % 21;
      const uint4 v = __ldg((const uint4*)(w + (size_t)k * (3 * DM) + (g / 7) * DM + cs * 56 + (g % 7) * 8));
      *(uint4*)((unsigned char*)g_w2 + (size_t)(set * 8 + cs) * W2_IMG + (k >> 6) * W2_CHUNK + g * W2_SBO + (k & 63) * 16) = v;
    }
  }
}
__device__ __forceinline__ void tile_w1(const __nv_bfloat16* w, int set, int kb, int cs, int t) {
  if (t < 196) {
    const int k = kb * 28 + t / 7, g = t % 7;
    const uint4 v = __ldg((const uint4*)(w + (size_t)k * DM + cs * 56 + g * 8));
    *(uint4*)((unsigned char*)g_w1 + (size_t)(set * 8 + cs) * W1_IMG + g * W1_SBO + k * 16) = v;
  }
}

__device__ __forceinline__ void put_w2(uint32_t sb, int set, int cs, int ch) {
  const uint32_t bar = sb + BARS + (B_W2RDY + ch) * 8;
  mbar_expect_tx(bar, W2_CHUNK);
  bulk_g2s(sb + w2_chunk_off(ch), (const unsigned char*)g_w2 + (size_t)(set * 8 + cs) * W2_IMG + ch * W2_CHUNK, W2_CHUNK, bar);
}

__global__ void __launch_bounds__(NTHREADS, 1)
mha_stack_kernel(const __nv_bfloat16* __restrict__ x, const __nv_bfloat16* __restrict__ wqkvA, const __nv_bfloat16* __restrict__ woA,
                 const __nv_bfloat16* __restrict__ wqkvB, const __nv_bfloat16* __restrict__ woB, __nv_bfloat16* __restrict__ out) {
  extern __shared__ __align__(1024) unsigned char smem[];
  constexpr uint32_t sb = SM_BASE, bars = sb + BARS;
  const int tid = threadIdx.x, wg = (tid >> 7) - 1, warp = (tid >> 5) & 3, lane = tid & 31;
  const int hi = blockIdx.x >> 3, lo = blockIdx.x & 7;
  if (tid == 0) {
    if ((uint32_t)__cvta_generic_to_shared(smem) != SM_BASE) __trap();
    for (int i = 0; i < 4; i++) {
      mbar_init(bars + (B_FULLKV + i) * 8, 1);
      mbar_init(bars + (B_EKV + i) * 8, 16);
      mbar_init(bars + (B_EP1 + i) * 8, 16);
      mbar_init(bars + (B_EP1 + 4 + i) * 8, 4);
      mbar_init(bars + (B_EP2 + i) * 8, 4);
      mbar_init(bars + (B_EP2 + 4 + i) * 8, 8);
      mbar_init(bars + (B_EKV0 + i) * 8, 8);
    }
    for (int i = 0; i < 16; i++) mbar_init(bars + (B_TP + i) * 8, 1);
    mbar_init(bars + B_W1RDY * 8, 1);
    for (int i = 0; i < 7; i++) mbar_init(bars + (B_W2RDY + i) * 8, 1);
    mbar_init(bars + B_W1FREE * 8, 8);
    mbar_init(bars + B_ZOK * 8, 1);
    asm volatile("fence.mbarrier_init.release.cluster;" ::: "memory");
  }
  const unsigned ep = *(volatile unsigned*)&g_epoch, ep4 = NLAYERS * ep;
  __syncthreads();
  PROFP(63);
  PROFC(62, true);

  if (wg < 0) {
    if (warp < 2) {
      const int hf = warp, rt = hf * 16 + hi;
      const bool issuer = lane == 0;
      auto put = [&](uint32_t ebar, uint32_t epar, uint32_t tbar, uint32_t dst, const unsigned char* src, uint32_t bytes) {
        mbar_wait(ebar, epar);
        if (issuer) {
          mbar_expect_tx(tbar, bytes);
          bulk_g2s(dst, src, bytes, tbar);
        }
      };
#pragma unroll 1
      for (int l = 0; l < NLAYERS; l++) {
        const int par = l & 1;
        {
          if (l == 0) {
            wait_flag(&g_flagY[rt * 32], 8u * (ep + 1));
            if (hf == 0) wait_flag(&g_flagW[lo * 32], 16u * (ep + 1));
            fence_proxy_async();
          } else {
            wait_canary(g_stats + ((par * NTILE + rt) * 64 + (lane >> 3) * 16 + 15) * 8 + (lane & 7), 4);
          }
          PROFP(l * 12 + 0);
          const uint32_t eb = bars + (B_EP2 + hf * 4) * 8, epar = par ^ hf ^ 1, tb = bars + (B_TP + (2 + hf) * 4) * 8;
          const unsigned char* src = (const unsigned char*)g_y + (size_t)(par * NTILE + rt) * ACT_TILE_BYTES;
          const bool first = l == 0 && hf == 0 && issuer;
          mbar_wait(eb, epar);
          if (issuer) {
            mbar_expect_tx(tb, 4096 + 16384);
            bulk_g2s(sb + STATS, g_stats + (par * NTILE + rt) * 512, 4096, tb);
            bulk_g2s(sb, src, 16384, tb);
          }
          if (first) { put_w2(sb, 0, lo, 0); put_w2(sb, 0, lo, 1); }
#pragma unroll 1
          for (int st = 1; st < 4; st++) {
            put(eb + st * 8, epar, tb + st * 8, sb + 2 * st * SLOT, src + 2 * st * 8192, st == 3 ? 8192 : 16384);
            if (first) { put_w2(sb, 0, lo, 2 * st); if (st < 3) put_w2(sb, 0, lo, 2 * st + 1); }
          }
        }
        if (hf == 0) {
          const unsigned char* kv = (const unsigned char*)g_kv + (size_t)(par * NH + hi) * NTILE * 8192;
          const unsigned* fq = &g_flagQ[(hi >> 1) * 32];
          const unsigned tq = ep4 + l + 1;
#pragma unroll 1
          for (int st = 0; st < 4; st++) {
            if ((st & 1) == 0) wait_flag4(fq + st * 2, tq);
            if (st == 0) PROFP(l * 12 + 2);
            put(bars + (B_EKV0 + st) * 8, par, bars + (B_FULLKV + st) * 8, sb + 2 * st * SLOT, kv + st * 16384, 16384);
          }
          PROFP(l * 12 + 4);
#pragma unroll 1
          for (int R = 1; R < 4; R++) {
#pragma unroll
            for (int st = 0; st < 4; st++) {
              const int j = R * 8 + st * 2;
              if ((st & 1) == 0) wait_flag4(fq + j, tq);
              if (st == 2 && R == 3) {
                const uint32_t km = ldcg32(&g_kmax[(par * NH + hi) * 16]);
                if (issuer) asm volatile("st.shared.u32 [%0], %1;" ::"r"(sb + KMAX + par * 4), "r"(km) : "memory");
              }
              put(bars + (B_EKV + st) * 8, (l + R + 1) & 1, bars + (B_FULLKV + st) * 8, sb + 2 * st * SLOT, kv + (size_t)j * 8192, 16384);
              if ((st & 1) == 0) {
                if (R == 1 && st == 0) {
                  if (l == 0) { wait_flag(&g_flagW[(8 + lo) * 32], 16u * (ep + 1)); fence_proxy_async(); }
                  if (issuer) {
                    mbar_expect_tx(bars + B_W1RDY * 8, W1_IMG);
                    bulk_g2s(sb + W1R, (const unsigned char*)g_w1 + (size_t)(par * 8 + lo) * W1_IMG, W1_IMG, bars + B_W1RDY * 8);
                  }
                } else if (l < NLAYERS - 1 && issuer) {
                  put_w2(sb, par ^ 1, lo, (j - 12) >> 2);
                }
              }
            }
          }
          PROFP(l * 12 + 5);
        } else if (l == 0) {
          wait_flag(&g_flagW[(8 + lo) * 32], 16u * (ep + 1));
        }
        mbar_wait(bars + B_ZOK * 8, par);
        {
          const unsigned char* src = (const unsigned char*)g_o + (size_t)rt * ACT_TILE_BYTES;
          wait_canary(src + (7 * ((lane & 15) >> 1) + 3) * 1024 + ((lane >> 4) * 16 + 15) * 16 + (lane & 1) * 8, 512);
          PROFP(l * 12 + 7);
#pragma unroll 1
          for (int st = 0; st < 4; st++)
            put(bars + (B_EP1 + hf * 4 + st) * 8, par, bars + (B_TP + hf * 4 + st) * 8, sb + 2 * st * SLOT, src + 2 * st * 8192, st == 3 ? 8192 : 16384);
        }
        if (hf == 1 && l < NLAYERS - 1) {
          mbar_wait(bars + B_W1FREE * 8, par);
          if (issuer) {
            put_w2(sb, par ^ 1, lo, 5);
            put_w2(sb, par ^ 1, lo, 6);
          }
        }
      }
    } else {
      {
        const int hf = warp - 2;
        const uint4 z4 = make_uint4(0, 0, 0, 0);
        if (hf == 0) publish<256>(3, &g_flagW[lo * 32], lane);
        publish<128>(1 + hf, &g_flagY[(hf * 16 + hi) * 32], lane);
        if (hf == 1) publish<256>(4, &g_flagW[(8 + lo) * 32], lane);
#pragma unroll 1
        for (int l = 0; l < NLAYERS; l++) {
          publish<256>(5 + hf, &g_flagQ[lo * 32 + hf * 16 + hi], lane);
          wait_flag(&g_flagQ[lo * 32 + lane], ep4 + l + 1);
          __syncwarp();
#pragma unroll
          for (int m = 0; m < 2; m++) {
            unsigned char* op = (unsigned char*)g_o + (size_t)(hf * 16 + lo * 2 + m) * ACT_TILE_BYTES + 7 * (hi >> 1) * 1024;
#pragma unroll
            for (int i = 0; i < 6; i++) *(uint4*)(op + (hi & 1) * 4096 + i * 512 + lane * 16) = z4;
#pragma unroll
            for (int i = 0; i < 2; i++) *(uint2*)(op + 3072 + (i * 32 + lane) * 16 + (hi & 1) * 8) = make_uint2(0, 0);
          }
          if (l < NLAYERS - 1) {
            const int np = (l & 1) ^ 1, rt = hf * 16 + hi;
            unsigned char* yp = (unsigned char*)g_y + (size_t)(np * NTILE + rt) * ACT_TILE_BYTES + lo * 7168 + lane * 16;
#pragma unroll
            for (int i = 0; i < 14; i++) *(uint4*)(yp + i * 512) = z4;
#pragma unroll
            for (int i = 0; i < 2; i++) g_stats[((np * NTILE + rt) * 64 + i * 32 + lane) * 8 + lo] = make_float2(0.f, 0.f);
#pragma unroll
            for (int e = 0; e < 2; e++) {
              const size_t hb = (size_t)(np * NH + 2 * lo + e) * NTILE;
#pragma unroll
              for (int i = 0; i < 8; i++) g_q[(hb + rt) * 256 + i * 32 + lane] = z4;
            }
          }
          __syncwarp();
          if (l == 1 && hf == 1 && lane == 0 && blockIdx.x == 0) *(volatile unsigned*)&g_epoch = ep + 1;
          if (lane == 0) red_release(&g_zcount);
          if (hf == 0) {
            __syncwarp();
            wait_flag(&g_zcount, 2u * NCTA * (ep4 + l + 1));
            if (lane == 0) mbar_arrive(bars + B_ZOK * 8);
          }
        }
      }
    }
  } else {
    const int half = wg >> 1;
    const int prt = half * 16 + hi;
    const int art = half * 16 + lo * 2 + (wg & 1);
    if ((wg & 1) == 0) {
      const __nv_bfloat16* xp = x + (size_t)(prt * 64 + warp * 16 + (lane >> 2)) * DM + lo * 56 + (lane & 3) * 2;
      uint32_t yv[14];
#pragma unroll
      for (int j = 0; j < 7; j++) {
        yv[2 * j] = *(const uint32_t*)(xp + j * 8);
        yv[2 * j + 1] = *(const uint32_t*)(xp + 8 * DM + j * 8);
      }
      store_y(yv, 0, prt, lo, warp, lane);
      hand_over<128>(1 + half);
    } else {
      const int t = half * 128 + (tid & 127);
      tile_w2(wqkvA, 0, hi, lo, t);
      hand_over<256>(3);
      tile_w1(woA, 0, hi, lo, t);
      tile_w2(wqkvB, 1, hi, lo, t);
      tile_w1(woB, 1, hi, lo, t);
      hand_over<256>(4);
    }
#pragma unroll 1
    for (int l = 0; l < NLAYERS; l++) {
      {
        float acc[44], rs[2];
        qkv_main(acc, rs, wg & 1, l, prt, half, sb, warp, lane);
        if ((wg & 1) == 0) qkv_store<0>(acc, rs, l, ep4, prt, lo, half, warp, lane);
        else qkv_store<1>(acc, rs, l, ep4, prt, lo, half, warp, lane);
      }
      attention(l, hi, art, wg, ep4, sb, warp, lane);
      if ((wg & 1) == 0) proj_out(l, prt, lo, half, out, sb, warp, lane);
      PROFP(l * 12 + 10);
    }
    PROFP(61);
    PROFC(60, true);
  }
}

}

extern "C" void kernel_launch(void* const* d_in, const int* in_sizes, int n_in, void* d_out, int out_size) {
  (void)in_sizes; (void)n_in; (void)out_size;
  static bool configured = false;
  if (!configured) {
    cudaFuncSetAttribute(mk::mha_stack_kernel, cudaFuncAttributeMaxDynamicSharedMemorySize, mk::SMEM_BYTES);
    configured = true;
  }
  mk::mha_stack_kernel<<<mk::NCTA, mk::NTHREADS, mk::SMEM_BYTES>>>(
      (const __nv_bfloat16*)d_in[0], (const __nv_bfloat16*)d_in[1], (const __nv_bfloat16*)d_in[2],
      (const __nv_bfloat16*)d_in[4], (const __nv_bfloat16*)d_in[5], (__nv_bfloat16*)d_out);
}
```

```cpp
#include <cuda_runtime.h>
#include <cuda_bf16.h>
#include <stdint.h>

namespace mk {

constexpr int SEQ = 2048, DM = 448, NH = 16, NTILE = 32, NCTA = 128, NTHREADS = 640;

constexpr uint32_t SM_BASE = 1024;
constexpr uint32_t SLOT = 8192;
constexpr uint32_t W2_SBO = 1024, W2_CHUNK = 21 * W2_SBO;
constexpr uint32_t W2H = 8 * SLOT;
constexpr uint32_t W1R = W2H + 5 * W2_CHUNK + 1024;
constexpr uint32_t W1_SBO = 7168;
constexpr uint32_t BARS = W1R + 7 * W1_SBO;
constexpr uint32_t KMAX = BARS + 624, KBAD = BARS + 632;
constexpr uint32_t STATS = BARS + 640;
constexpr uint32_t SMEM_BYTES = STATS + 4096;
enum { B_FULLKV = 0  , B_EKV = 8  , B_EKV3 = 16  , B_REL1 = 24  , B_REL2 = 32  ,
       B_TP1 = 40  , B_TP2 = 48  , B_TKV0 = 56, B_W1RDY = 58, B_W2RDY = 59, B_W1FREE = 66,
       B_ZOK = 67, B_WFREE = 68  , B_COUNT = 70 };
__host__ __device__ constexpr uint32_t w2_chunk_off(int ch) { return W2H + ch * W2_CHUNK + (ch >= 3 ? 1024 : 0); }

#define JM0_V 0xB6
#define JM1_V 0xB6
constexpr uint32_t JM0 = JM0_V, JM1 = JM1_V;

constexpr int ACT_TILE_BYTES = 64 * DM * 2;
__device__ uint4 g_y[2 * NTILE * ACT_TILE_BYTES / 16];
__device__ uint4 g_o[NTILE * ACT_TILE_BYTES / 16];
__device__ uint4 g_q[2 * NH * NTILE * 256];
__device__ uint4 g_kv[2 * NH * NTILE * 512];
__device__ __align__(16) float2 g_stats[2 * NTILE * 64 * 8];
__device__ unsigned long long g_kmax[2 * NH * 16];
constexpr int W2_IMG = 7 * W2_CHUNK, W1_IMG = 7 * W1_SBO;
__device__ uint4 g_w2[2 * 8 * W2_IMG / 16];
__device__ uint4 g_w1[2 * 8 * W1_IMG / 16];
__device__ unsigned g_flagW[2 * 8 * 32];
__device__ unsigned g_flagY[NTILE * 32], g_zcount;
__device__ __align__(128) unsigned g_flagQ[8 * 32];
__device__ unsigned g_epoch;

#define NLAYERS 4

__device__ __forceinline__ void wg_fence() { asm volatile("wgmma.fence.sync.aligned;" ::: "memory"); }
__device__ __forceinline__ void wg_commit() { asm volatile("wgmma.commit_group.sync.aligned;" ::: "memory"); }
template <int N> __device__ __forceinline__ void wg_wait() { asm volatile("wgmma.wait_group.sync.aligned %0;" ::"n"(N) : "memory"); }
__host__ __device__ constexpr uint64_t mkdesc(uint32_t off, uint32_t lbo, uint32_t sbo) {
  return (uint64_t)(((SM_BASE + off) & 0x3FFFF) >> 4) | ((uint64_t)(lbo >> 4) << 16) | ((uint64_t)(sbo >> 4) << 32);
}
template <int N> __device__ __forceinline__ void fence_regs(float (&r)[N]) {
#pragma unroll
  for (int i = 0; i < N; i++) asm volatile("" : "+f"(r[i])::"memory");
}
template <int N> __device__ __forceinline__ void fence_regs(uint32_t (&r)[N]) {
#pragma unroll
  for (int i = 0; i < N; i++) asm volatile("" : "+r"(r[i])::"memory");
}
__device__ __forceinline__ void mbar_init(uint32_t bar, uint32_t cnt) { asm volatile("mbarrier.init.shared::cta.b64 [%0], %1;" ::"r"(bar), "r"(cnt) : "memory"); }
__device__ __forceinline__ void mbar_expect_tx(uint32_t bar, uint32_t bytes) {
  asm volatile("mbarrier.arrive.expect_tx.shared::cta.b64 _, [%0], %1;" ::"r"(bar), "r"(bytes) : "memory");
}
__device__ __forceinline__ void mbar_arrive(uint32_t bar) { asm volatile("mbarrier.arrive.shared::cta.b64 _, [%0];" ::"r"(bar) : "memory"); }
__device__ __forceinline__ void mbar_wait(uint32_t bar, uint32_t parity) {
  asm volatile(
      "{\n.reg .pred p;\n.reg .u32 c;\n"
      "mov.u32 c, 0;\n"
      "AGAIN:\n"
      "mbarrier.try_wait.parity.shared::cta.b64 p, [%0], %1;\n"
      "@p bra DONE;\n"
      "add.u32 c, c, 1;\n"
      "setp.lt.u32 p, c, 0x4000000;\n"
      "@p bra AGAIN;\n"
      "trap;\n"
      "DONE:\n}\n" ::"r"(bar), "r"(parity) : "memory");
}
__device__ __forceinline__ uint32_t mbar_test(uint32_t bar, uint32_t parity) {
  uint32_t ok;
  asm volatile("{\n.reg .pred p;\nmbarrier.test_wait.parity.shared::cta.b64 p, [%1], %2;\nselp.u32 %0, 1, 0, p;\n}\n" : "=r"(ok) : "r"(bar), "r"(parity) : "memory");
  return ok;
}
__device__ __forceinline__ void bulk_g2s(uint32_t dst, const void* src, uint32_t bytes, uint32_t bar) {
  asm volatile("cp.async.bulk.shared::cluster.global.mbarrier::complete_tx::bytes [%0], [%1], %2, [%3];" ::"r"(dst), "l"(src), "r"(bytes), "r"(bar) : "memory");
}
__device__ __forceinline__ void fence_proxy_async() { asm volatile("fence.proxy.async.global;" ::: "memory"); }
__device__ __forceinline__ unsigned ld_relaxed(const unsigned* p) {
  unsigned v;
  asm volatile("ld.relaxed.gpu.global.u32 %0, [%1];" : "=r"(v) : "l"(p) : "memory");
  return v;
}
__device__ __forceinline__ void fence_acquire() { asm volatile("fence.acquire.gpu;" ::: "memory"); }
__device__ __forceinline__ void red_release(unsigned* p) { asm volatile("red.release.gpu.global.add.u32 [%0], 1;" ::"l"(p) : "memory"); }
__device__ __forceinline__ void wait_flag(const unsigned* p, unsigned target) {
  uint32_t it = 0;
  while ((int)(ld_relaxed(p) - target) < 0)
    if (++it > (1u << 22)) __trap();
  fence_acquire();
}
__device__ __forceinline__ void wait_flag4(const unsigned* p, unsigned target) {
  uint32_t it = 0, a, b, c, d;
  do {
    asm volatile("ld.relaxed.gpu.global.v4.u32 {%0, %1, %2, %3}, [%4];" : "=r"(a), "=r"(b), "=r"(c), "=r"(d) : "l"(p) : "memory");
    if (++it > (1u << 22)) __trap();
  } while ((int)((a - target) | (b - target) | (c - target) | (d - target)) < 0);
  fence_acquire();
  fence_proxy_async();
}
template <int NT> __device__ __forceinline__ void hand_over(int barid) {
  fence_proxy_async();
  asm volatile("bar.arrive %0, %1;" ::"r"(barid), "n"(NT + 32) : "memory");
}
template <int NT> __device__ __forceinline__ void publish(int barid, unsigned* flag, int lane) {
  asm volatile("bar.sync %0, %1;" ::"r"(barid), "n"(NT + 32) : "memory");
  if (lane == 0) red_release(flag);
}
__device__ __forceinline__ uint32_t ldcg32(const void* p) {
  uint32_t v;
  asm volatile("ld.global.cg.u32 %0, [%1];" : "=r"(v) : "l"(p) : "memory");
  return v;
}
__device__ __forceinline__ uint32_t lds32(uint32_t a) {
  uint32_t v;
  asm volatile("ld.shared.u32 %0, [%1];" : "=r"(v) : "r"(a) : "memory");
  return v;
}
__device__ __forceinline__ void stg32(void* p, uint32_t v) { asm volatile("st.global.u32 [%0], %1;" ::"l"(p), "r"(v) : "memory"); }
__device__ __forceinline__ void st_word(void* p, uint32_t v) { asm volatile("st.relaxed.gpu.global.u32 [%0], %1;" ::"l"(p), "r"(max(v, 1u)) : "memory"); }
__device__ __forceinline__ uint4 ld_piece(const void* p) {
  uint4 v;
  asm volatile("ld.relaxed.gpu.global.v4.u32 {%0, %1, %2, %3}, [%4];" : "=r"(v.x), "=r"(v.y), "=r"(v.z), "=r"(v.w) : "l"(p) : "memory");
  return v;
}
__device__ __forceinline__ bool missing(const uint4& v) { return v.x == 0 || v.y == 0 || v.z == 0 || v.w == 0; }
__device__ __forceinline__ uint4 lds128(uint32_t a) {
  uint4 v;
  asm volatile("ld.shared.v4.u32 {%0, %1, %2, %3}, [%4];" : "=r"(v.x), "=r"(v.y), "=r"(v.z), "=r"(v.w) : "r"(a) : "memory");
  return v;
}
__device__ __forceinline__ uint4 repair(const void* src) {
  uint4 v;
  uint32_t it = 0;
  do {
    v = ld_piece(src);
    if (++it > (1u << 22)) __trap();
  } while (missing(v));
  return v;
}
__device__ __forceinline__ void wait_canary(const void* p, int delta) {
  const unsigned *pa = (const unsigned*)p, *pb = (const unsigned*)((const unsigned char*)p + delta);
  uint32_t a0 = ld_relaxed(pa), b0 = ld_relaxed(pb), it = 0;
  while (true) {
    const uint32_t a1 = ld_relaxed(pa), b1 = ld_relaxed(pb);
    if (__all_sync(0xffffffffu, a0 != 0 && b0 != 0)) break;
    a0 = ld_relaxed(pa); b0 = ld_relaxed(pb);
    if (__all_sync(0xffffffffu, a1 != 0 && b1 != 0)) break;
    if (++it > (1u << 21)) __trap();
  }
  fence_proxy_async();
}
__device__ __forceinline__ void wait_canary_lanes(const void* p, int delta, uint32_t mask, uint32_t& seen) {
  uint32_t it = 0;
  while ((seen & mask) != mask) {
    const uint32_t a = ld_relaxed((const unsigned*)p), b = ld_relaxed((const unsigned*)((const unsigned char*)p + delta));
    seen = __ballot_sync(0xffffffffu, a != 0 && b != 0);
    if (++it > (1u << 22)) __trap();
    fence_proxy_async();
  }
}
__device__ __forceinline__ uint32_t pack_bf16(float lo, float hi) {
  uint32_t r;
  asm("cvt.rn.bf16x2.f32 %0, %1, %2;" : "=r"(r) : "f"(hi), "f"(lo));
  return r;
}
__device__ __forceinline__ float bf_lo(uint32_t v) { return __uint_as_float(v << 16); }
__device__ __forceinline__ float bf_hi(uint32_t v) { return __uint_as_float(v & 0xFFFF0000u); }
__device__ __forceinline__ float ex2(float x) {
  float e;
  asm("ex2.approx.ftz.f32 %0, %1;" : "=f"(e) : "f"(x));
  return e;
}
__device__ __forceinline__ float quad_sum(float v) {
  v += __shfl_xor_sync(0xffffffffu, v, 1);
  v += __shfl_xor_sync(0xffffffffu, v, 2);
  return v;
}

template <int ACC>
__device__ __forceinline__ void wgmma_qk(float (&d)[32], uint32_t a0, uint32_t a1, uint32_t a2, uint32_t a3, uint64_t descB) {
  asm volatile(
      "{\n.reg .pred p;\nsetp.ne.b32 p, %37, 0;\n"
      "wgmma.mma_async.sync.aligned.m64n64k16.f32.bf16.bf16 {"
      "%0, %1, %2, %3, %4, %5, %6, %7, %8, %9, %10, %11, %12, %13, %14, %15,"
      "%16, %17, %18, %19, %20, %21, %22, %23, %24, %25, %26, %27, %28, %29, %30, %31}, "
      "{%32, %33, %34, %35}, %36, p, 1, 1, 0;\n}\n"
      : "+f"(d[0]), "+f"(d[1]), "+f"(d[2]), "+f"(d[3]), "+f"(d[4]), "+f"(d[5]), "+f"(d[6]), "+f"(d[7]),
      "+f"(d[8]), "+f"(d[9]), "+f"(d[10]), "+f"(d[11]), "+f"(d[12]), "+f"(d[13]), "+f"(d[14]), "+f"(d[15]),
      "+f"(d[16]), "+f"(d[17]), "+f"(d[18]), "+f"(d[19]), "+f"(d[20]), "+f"(d[21]), "+f"(d[22]), "+f"(d[23]),
      "+f"(d[24]), "+f"(d[25]), "+f"(d[26]), "+f"(d[27]), "+f"(d[28]), "+f"(d[29]), "+f"(d[30]), "+f"(d[31])
      : "r"(a0), "r"(a1), "r"(a2), "r"(a3), "l"(descB), "n"(ACC));
}

template <int ACC>
__device__ __forceinline__ void wgmma_pv(float (&d)[16], uint32_t a0, uint32_t a1, uint32_t a2, uint32_t a3, uint64_t descB) {
  asm volatile(
      "{\n.reg .pred p;\nsetp.ne.b32 p, %21, 0;\n"
      "wgmma.mma_async.sync.aligned.m64n32k16.f32.bf16.bf16 {"
      "%0, %1, %2, %3, %4, %5, %6, %7, %8, %9, %10, %11, %12, %13, %14, %15}, "
      "{%16, %17, %18, %19}, %20, p, 1, 1, 1;\n}\n"
      : "+f"(d[0]), "+f"(d[1]), "+f"(d[2]), "+f"(d[3]), "+f"(d[4]), "+f"(d[5]), "+f"(d[6]), "+f"(d[7]),
      "+f"(d[8]), "+f"(d[9]), "+f"(d[10]), "+f"(d[11]), "+f"(d[12]), "+f"(d[13]), "+f"(d[14]), "+f"(d[15])
      : "r"(a0), "r"(a1), "r"(a2), "r"(a3), "l"(descB), "n"(ACC));
}

template <int ACC>
__device__ __forceinline__ void wgmma_p1(float (&d)[28], uint64_t descA, uint64_t descB) {
  asm volatile(
      "{\n.reg .pred p;\nsetp.ne.b32 p, %30, 0;\n"
      "wgmma.mma_async.sync.aligned.m64n56k16.f32.bf16.bf16 {"
      "%0, %1, %2, %3, %4, %5, %6, %7, %8, %9, %10, %11, %12, %13, %14, %15,"
      "%16, %17, %18, %19, %20, %21, %22, %23, %24, %25, %26, %27}, "
      "%28, %29, p, 1, 1, 0, 1;\n}\n"
      : "+f"(d[0]), "+f"(d[1]), "+f"(d[2]), "+f"(d[3]), "+f"(d[4]), "+f"(d[5]), "+f"(d[6]), "+f"(d[7]),
      "+f"(d[8]), "+f"(d[9]), "+f"(d[10]), "+f"(d[11]), "+f"(d[12]), "+f"(d[13]), "+f"(d[14]), "+f"(d[15]),
      "+f"(d[16]), "+f"(d[17]), "+f"(d[18]), "+f"(d[19]), "+f"(d[20]), "+f"(d[21]), "+f"(d[22]), "+f"(d[23]),
      "+f"(d[24]), "+f"(d[25]), "+f"(d[26]), "+f"(d[27])
      : "l"(descA), "l"(descB), "n"(ACC));
}

template <int ACC>
__device__ __forceinline__ void wgmma_p2(float (&d)[44], uint32_t a0, uint32_t a1, uint32_t a2, uint32_t a3, uint64_t descB) {
  asm volatile(
      "{\n.reg .pred p;\nsetp.ne.b32 p, %49, 0;\n"
      "wgmma.mma_async.sync.aligned.m64n88k16.f32.bf16.bf16 {"
      "%0, %1, %2, %3, %4, %5, %6, %7, %8, %9, %10, %11, %12, %13, %14, %15,"
      "%16, %17, %18, %19, %20, %21, %22, %23, %24, %25, %26, %27, %28, %29, %30, %31,"
      "%32, %33, %34, %35, %36, %37, %38, %39, %40, %41, %42, %43}, "
      "{%44, %45, %46, %47}, %48, p, 1, 1, 1;\n}\n"
      : "+f"(d[0]), "+f"(d[1]), "+f"(d[2]), "+f"(d[3]), "+f"(d[4]), "+f"(d[5]), "+f"(d[6]), "+f"(d[7]),
      "+f"(d[8]), "+f"(d[9]), "+f"(d[10]), "+f"(d[11]), "+f"(d[12]), "+f"(d[13]), "+f"(d[14]), "+f"(d[15]),
      "+f"(d[16]), "+f"(d[17]), "+f"(d[18]), "+f"(d[19]), "+f"(d[20]), "+f"(d[21]), "+f"(d[22]), "+f"(d[23]),
      "+f"(d[24]), "+f"(d[25]), "+f"(d[26]), "+f"(d[27]), "+f"(d[28]), "+f"(d[29]), "+f"(d[30]), "+f"(d[31]),
      "+f"(d[32]), "+f"(d[33]), "+f"(d[34]), "+f"(d[35]), "+f"(d[36]), "+f"(d[37]), "+f"(d[38]), "+f"(d[39]),
      "+f"(d[40]), "+f"(d[41]), "+f"(d[42]), "+f"(d[43])
      : "r"(a0), "r"(a1), "r"(a2), "r"(a3), "l"(descB), "n"(ACC));
}

__device__ __forceinline__ uint32_t exp_mufu(float x0, float x1) { return pack_bf16(ex2(x0), ex2(x1)); }
__device__ __forceinline__ uint32_t exp_poly(float x0, float x1, uint32_t c2) {
  uint32_t t0 = __float_as_uint(x0), t1 = __float_as_uint(x1), u, n, h, r;
  asm("prmt.b32 %0, %1, %2, 0xF5B1;" : "=r"(u) : "r"(t0), "r"(t1));
  asm("prmt.b32 %0, %1, %2, 0xF6B2;" : "=r"(n) : "r"(t0), "r"(t1));
  asm("fma.rn.f16x2 %0, %1, %2, %3;" : "=r"(h) : "r"(c2), "r"(u), "r"(0x353C353Cu));
  asm("fma.rn.f16x2 %0, %1, %2, %3;" : "=r"(h) : "r"(h), "r"(u), "r"(0x04000400u));
  asm("mad.lo.u32 %0, %1, 128, %2;" : "=r"(r) : "r"(n), "r"(h));
  return r;
}
template <uint32_t JM, int LO, int HI> __device__ __forceinline__ void softmax_tile(const float (&s)[32], uint32_t (&p)[16], uint32_t c2) {
#pragma unroll
  for (int i = LO; i < HI; i++) p[i] = ((JM >> (i >> 1)) & 1) ? exp_poly(s[2 * i], s[2 * i + 1], c2) : exp_mufu(s[2 * i], s[2 * i + 1]);
}
template <int SL> __device__ __forceinline__ void issue_qk(float (&s)[32], const uint32_t (&q)[8], uint64_t db) {
  wgmma_qk<0>(s, q[0], q[1], q[2], q[3], db + (SL * SLOT >> 4));
  wgmma_qk<1>(s, q[4], q[5], q[6], q[7], db + ((SL * SLOT + 256) >> 4));
}
template <int SL> __device__ __forceinline__ void issue_pv(float (&o)[16], uint32_t (&p)[16], uint64_t db) {
  fence_regs(p);
  wg_fence();
#pragma unroll
  for (int j = 0; j < 4; j++) wgmma_pv<1>(o, p[4 * j], p[4 * j + 1], p[4 * j + 2], p[4 * j + 3], db + ((SL * SLOT + 4096 + (j >> 1) * 2048 + (j & 1) * 256) >> 4));
}
template <int I>
__device__ __forceinline__ void att_step(float (&s)[32], float (&o)[16], const uint32_t (&q)[8], uint32_t (&p)[16], uint32_t ecur, uint32_t par,
                                         uint32_t pass, uint32_t c2, int lane, uint32_t& rdy, uint64_t db) {
  constexpr int ST = (((I | 1) + 1) / 2) & 7;
  constexpr uint32_t fw = SM_BASE + BARS + (B_FULLKV + ST) * 8;
  const uint32_t pw = ST < 2 ? par : pass;
  issue_pv<I>(o, p, db);
  wg_commit();
  if ((I & 1) && !rdy) mbar_wait(fw, pw);
  wg_wait<0>();
  fence_regs(o);
  wg_fence();
  issue_qk<(I + 1) & 15>(s, q, db);
  wg_commit();
  if ((I & 1) && lane == 0) mbar_arrive(ecur + (I / 2) * 8);
  if (!(I & 1)) rdy = mbar_test(fw, pw) | (I == 0 ? pass ^ 1 : 0u);
  wg_wait<0>();
  fence_regs(s);
  softmax_tile<(I & 1) ? JM0 : JM1, 0, 16>(s, p, c2);
}

__device__ __forceinline__ void mma16816(float (&d)[4], uint32_t a0, uint32_t a1, uint32_t a2, uint32_t a3, uint32_t b0, uint32_t b1) {
  asm volatile("mma.sync.aligned.m16n8k16.row.col.f32.bf16.bf16.f32 {%0,%1,%2,%3}, {%4,%5,%6,%7}, {%8,%9}, {%0,%1,%2,%3};"
               : "+f"(d[0]), "+f"(d[1]), "+f"(d[2]), "+f"(d[3])
               : "r"(a0), "r"(a1), "r"(a2), "r"(a3), "r"(b0), "r"(b1));
}
__device__ __forceinline__ void attend_safe(float* o_out, const uint32_t* q_in, const unsigned char* kv, int lane) {
  uint32_t q[8];
#pragma unroll
  for (int i = 0; i < 8; i++) q[i] = q_in[i];
  float o[4][4];
#pragma unroll
  for (int i = 0; i < 16; i++) o[i >> 2][i & 3] = 0.f;
  float m0 = -INFINITY, m1 = -INFINITY;
  const int c = lane & 3, r = lane >> 2;
#pragma unroll 1
  for (int blk = 0; blk < SEQ / 16; blk++) {
    const unsigned char* kb = kv + (size_t)(blk >> 2) * 8192 + (blk & 3) * 1024;
    float s[2][4];
#pragma unroll
    for (int n = 0; n < 2; n++) {
#pragma unroll
      for (int i = 0; i < 4; i++) s[n][i] = 0.f;
      const unsigned char* kp = kb + n * 512 + lane * 4;
      mma16816(s[n], q[0], q[1], q[2], q[3], ldcg32(kp), ldcg32(kp + 128));
      mma16816(s[n], q[4], q[5], q[6], q[7], ldcg32(kp + 256), ldcg32(kp + 384));
    }
    float t0 = fmaxf(fmaxf(s[0][0], s[0][1]), fmaxf(s[1][0], s[1][1]));
    float t1 = fmaxf(fmaxf(s[0][2], s[0][3]), fmaxf(s[1][2], s[1][3]));
    t0 = fmaxf(t0, __shfl_xor_sync(0xffffffffu, t0, 1)); t0 = fmaxf(t0, __shfl_xor_sync(0xffffffffu, t0, 2));
    t1 = fmaxf(t1, __shfl_xor_sync(0xffffffffu, t1, 1)); t1 = fmaxf(t1, __shfl_xor_sync(0xffffffffu, t1, 2));
    const float n0 = fmaxf(m0, t0), n1 = fmaxf(m1, t1);
    const float f0 = ex2(m0 - n0), f1 = ex2(m1 - n1);
    m0 = n0; m1 = n1;
    const uint32_t a0 = pack_bf16(ex2(s[0][0] - n0), ex2(s[0][1] - n0)), a1 = pack_bf16(ex2(s[0][2] - n1), ex2(s[0][3] - n1));
    const uint32_t a2 = pack_bf16(ex2(s[1][0] - n0), ex2(s[1][1] - n0)), a3 = pack_bf16(ex2(s[1][2] - n1), ex2(s[1][3] - n1));
#pragma unroll
    for (int dg = 0; dg < 4; dg++) {
      o[dg][0] *= f0; o[dg][1] *= f0; o[dg][2] *= f1; o[dg][3] *= f1;
      const unsigned char* vp = kv + (size_t)(blk >> 2) * 8192 + 4096 + ((blk >> 1) & 1) * 2048 + (blk & 1) * 256 + dg * 512 + c * 32 + (r >> 1) * 4;
      const uint32_t sel = (r & 1) ? 0x7632 : 0x5410;
      const uint32_t b0 = __byte_perm(ldcg32(vp), ldcg32(vp + 16), sel);
      const uint32_t b1 = __byte_perm(ldcg32(vp + 128), ldcg32(vp + 144), sel);
      mma16816(o[dg], a0, a1, a2, a3, b0, b1);
    }
  }
#pragma unroll
  for (int i = 0; i < 16; i++) o_out[i] = o[i >> 2][i & 3];
}

__device__ __forceinline__ void attention(int layer, int h, int rt, int wg, unsigned ep4, uint32_t sb, int warp, int lane, uint64_t db) {
  const uint32_t bars = sb + BARS;
  const int par = layer & 1;
  if (layer == 0) {
    if (lane == 0) wait_flag(&g_flagQ[(h >> 1) * 32 + rt], ep4 + 1);
    __syncwarp();
  }
  uint32_t q[8];
  const unsigned char* qp = (const unsigned char*)g_q + ((size_t)(par * NH + h) * NTILE + rt) * 4096 + warp * 1024 + lane * 4;
  {
    uint32_t it = 0;
    do {
#pragma unroll
      for (int i = 0; i < 8; i++) q[i] = ld_relaxed((const unsigned*)(qp + (i & 1) * 512 + (i >> 1) * 128));
      if (++it > (1u << 22)) __trap();
    } while (q[0] == 0 || q[1] == 0 || q[2] == 0 || q[3] == 0 || q[4] == 0 || q[5] == 0 || q[6] == 0 || q[7] == 0);
    __syncwarp();
  }
  const int c = lane & 3, odd = h & 1;
  const bool padlane = odd ? (c < 2) : (c >= 2);
  uint32_t c2 = 0x71627162u;
  asm volatile("" : "+r"(c2));
  float s[32], o[16];
  uint32_t p[16];
#pragma unroll
  for (int i = 0; i < 16; i++) o[i] = 0.f;
  fence_regs(o);
  mbar_wait(bars + B_TKV0 * 8, par);
  wg_fence();
  issue_qk<0>(s, q, db);
  wg_commit();
  float qn;
  {
    float qa = 0.f, qb = 0.f;
#pragma unroll
    for (int i = 0; i < 8; i += 2) {
      const uint32_t u = (i == 6 && padlane) ? 0u : q[i], v = (i == 6 && padlane) ? 0u : q[i + 1];
      qa += bf_lo(u) * bf_lo(u) + bf_hi(u) * bf_hi(u);
      qb += bf_lo(v) * bf_lo(v) + bf_hi(v) * bf_hi(v);
    }
    qn = fmaxf(quad_sum(qa), quad_sum(qb));
  }
  if (wg < 2) {
    uint32_t m = 0xffffffffu;
#pragma unroll
    for (int i = 0; i < 8; i++) {
      const uint4 v = lds128(sb + (threadIdx.x - 128) * 16 + i * 4096);
      m = min(min(m, min(v.x, v.y)), min(v.z, v.w));
    }
    if (m == 0) asm volatile("st.shared.u32 [%0], %1;" ::"r"(sb + KBAD), "r"(layer + 1) : "memory");
  }
  wg_wait<0>();
  fence_regs(s);
  softmax_tile<JM0, 0, 16>(s, p, c2);
  uint32_t rdy = 0;
#pragma unroll 1
  for (uint32_t pass = 0; pass < 2; pass++) {
    const uint32_t ecur = bars + (pass ? B_EKV3 : B_EKV) * 8;
#define STEP(I) att_step<I>(s, o, q, p, ecur, par, pass, c2, lane, rdy, db);
    STEP(0) STEP(1) STEP(2) STEP(3) STEP(4) STEP(5) STEP(6) STEP(7) STEP(8) STEP(9) STEP(10) STEP(11) STEP(12) STEP(13) STEP(14)
    if (pass) break;
    STEP(15)
#undef STEP
  }
  issue_pv<15>(o, p, db);
  wg_commit();
  mbar_wait(bars + B_ZOK * 8, par);
  const float km = __uint_as_float(lds32(sb + KMAX + par * 4));
  wg_wait<0>();
  fence_regs(o);
  if (lane == 0) mbar_arrive(bars + (B_EKV3 + 7) * 8);
  const int lsrc = (lane & ~3) | (odd ? 0 : 2);
  float la = __shfl_sync(0xffffffffu, o[12], lsrc), lb = __shfl_sync(0xffffffffu, o[14], lsrc);
  const float lo_lim = 8.0779357e-28f  , hi_lim = 512.f;
  const bool ok = lds32(sb + KBAD) != (uint32_t)layer + 1 && (qn * km <= 124.f * 124.f) && la >= lo_lim && la < hi_lim && lb >= lo_lim && lb < hi_lim;
  if (!__all_sync(0xffffffffu, ok)) {
    float ot[16];
    if (padlane) { q[6] = 0; q[7] = 0; }
    attend_safe(ot, q, (const unsigned char*)g_kv + (size_t)(par * NH + h) * NTILE * 8192, lane);
#pragma unroll
    for (int i = 0; i < 16; i++) o[i] = ot[i];
    la = __shfl_sync(0xffffffffu, o[12], lsrc);
    lb = __shfl_sync(0xffffffffu, o[14], lsrc);
  }
  const float ia = __fdividef(1.f, la), ib = __fdividef(1.f, lb);
  unsigned char* op = (unsigned char*)g_o + (size_t)rt * ACT_TILE_BYTES + (7 * (h >> 1)) * 1024 + warp * 256 + lane * 4;
#pragma unroll
  for (int j = 0; j < 3; j++) {
    st_word(op + (j + 4 * odd) * 1024, pack_bf16(o[4 * j] * ia, o[4 * j + 1] * ia));
    st_word(op + (j + 4 * odd) * 1024 + 128, pack_bf16(o[4 * j + 2] * ib, o[4 * j + 3] * ib));
  }
  if (!padlane) {
    st_word(op + 3 * 1024, pack_bf16(o[12] * ia, o[13] * ia));
    st_word(op + 3 * 1024 + 128, pack_bf16(o[14] * ib, o[15] * ib));
  }
}

__device__ __forceinline__ void pack_y(uint32_t (&w)[15], const float (&y)[28], int lane) {
  float sa = 0.f, sb = 0.f, va = 0.f, vb = 0.f;
#pragma unroll
  for (int j = 0; j < 7; j++) {
    w[2 * j] = pack_bf16(y[4 * j], y[4 * j + 1]);
    w[2 * j + 1] = pack_bf16(y[4 * j + 2], y[4 * j + 3]);
    sa += y[4 * j] + y[4 * j + 1];
    sb += y[4 * j + 2] + y[4 * j + 3];
    va = fmaf(y[4 * j], y[4 * j], fmaf(y[4 * j + 1], y[4 * j + 1], va));
    vb = fmaf(y[4 * j + 2], y[4 * j + 2], fmaf(y[4 * j + 3], y[4 * j + 3], vb));
  }
  const int c = lane & 3;
  float u = (c & 1) ? va : sa, v = (c & 1) ? vb : sb;
  u += __shfl_xor_sync(0xffffffffu, (c & 1) ? sa : va, 1);
  v += __shfl_xor_sync(0xffffffffu, (c & 1) ? sb : vb, 1);
  float r = (c & 2) ? v : u;
  r += __shfl_xor_sync(0xffffffffu, (c & 2) ? u : v, 2);
  w[14] = __float_as_uint(r);
}
__device__ __forceinline__ void store_y(const uint32_t (&w)[15], int par, int rt, int cs, int warp, int lane) {
  unsigned char* yp = (unsigned char*)g_y + (size_t)(par * NTILE + rt) * ACT_TILE_BYTES + (7 * cs) * 1024 + warp * 256 + lane * 4;
#pragma unroll
  for (int i = 0; i < 14; i++) st_word(yp + (i >> 1) * 1024 + (i & 1) * 128, w[i]);
  st_word((unsigned*)(g_stats + ((par * NTILE + rt) * 64 + warp * 16 + (lane >> 2) + ((lane >> 1) & 1) * 8) * 8 + cs) + (lane & 1), w[14]);
}

__device__ __forceinline__ uint32_t sub_bf16x2(uint32_t a, uint32_t b) {
  uint32_t r;
  asm("sub.rn.bf16x2 %0, %1, %2;" : "=r"(r) : "r"(a), "r"(b));
  return r;
}
template <int NK> __device__ __forceinline__ void load_frags(uint32_t (&x)[NK][4], uint32_t addr) {
#pragma unroll
  for (int i = 0; i < NK; i++)
    asm volatile("ldmatrix.sync.aligned.m8n8.x4.shared.b16 {%0,%1,%2,%3}, [%4];"
                 : "=r"(x[i][0]), "=r"(x[i][1]), "=r"(x[i][2]), "=r"(x[i][3]) : "r"(addr + i * 2048) : "memory");
}
template <int NK> __device__ __forceinline__ uint32_t min_frags(uint32_t m, const uint32_t (&x)[NK][4]) {
#pragma unroll
  for (int i = 0; i < NK; i++) m = min(min(m, min(x[i][0], x[i][1])), min(x[i][2], x[i][3]));
  return m;
}
template <int NG, bool W2>
__device__ __forceinline__ void redo_rows(float (&acc)[4 * NG], const unsigned char* gsrc, uint32_t m0, uint32_t m1, uint32_t woff, int lane) {
#pragma unroll
  for (int i = 0; i < 4 * NG; i++) acc[i] = 0.f;
#pragma unroll 1
  for (int ks = 0; ks < 28; ks++) {
    uint32_t x[4], it = 0;
    do {
#pragma unroll
      for (int i = 0; i < 4; i++) x[i] = ld_relaxed((const unsigned*)(gsrc + ks * 2048 + (i >> 1) * 1024 + (i & 1) * 128));
      if (++it > (1u << 22)) __trap();
    } while (x[0] == 0 || x[1] == 0 || x[2] == 0 || x[3] == 0);
    __syncwarp();
    x[0] = sub_bf16x2(x[0], m0); x[1] = sub_bf16x2(x[1], m1); x[2] = sub_bf16x2(x[2], m0); x[3] = sub_bf16x2(x[3], m1);
    const uint32_t wa = SM_BASE + woff + (W2 ? w2_chunk_off(ks >> 2) + (ks & 3) * 256 : W1R + ks * 256) + (lane & 15) * 16;
#pragma unroll
    for (int j = 0; j < NG; j++) {
      uint32_t b0, b1;
      asm volatile("ldmatrix.sync.aligned.m8n8.x2.trans.shared.b16 {%0,%1}, [%2];" : "=r"(b0), "=r"(b1) : "r"(wa + j * (W2 ? W2_SBO : W1_SBO)) : "memory");
      float d[4] = {acc[4 * j], acc[4 * j + 1], acc[4 * j + 2], acc[4 * j + 3]};
      mma16816(d, x[0], x[1], x[2], x[3], b0, b1);
      acc[4 * j] = d[0]; acc[4 * j + 1] = d[1]; acc[4 * j + 2] = d[2]; acc[4 * j + 3] = d[3];
    }
  }
}
#define NEED_REDO(chk) __any_sync(0xffffffffu, (chk) == 0)

__device__ __forceinline__ uint32_t pair_all(uint32_t ok, int half) {
  uint32_t r;
  asm volatile("{\n.reg .pred p, q;\nsetp.ne.u32 p, %1, 0;\nbar.red.and.pred q, %2, 256, p;\nselp.u32 %0, 1, 0, q;\n}\n"
               : "=r"(r) : "r"(ok), "r"(7 + half) : "memory");
  return r;
}
__device__ __forceinline__ void proj_out_check(int layer, int half, uint32_t sb, int lane) {
  const uint32_t bars = sb + BARS;
  uint32_t m = 0xffffffffu;
#pragma unroll 1
  for (int st = 0; st < 4; st++) {
    const uint32_t a = sb + ((st + 2 * half) & 3) * 2 * SLOT + (threadIdx.x & 127) * 16;
    mbar_wait(bars + (B_TP1 + half * 4 + st) * 8, layer & 1);
#pragma unroll
    for (int i = 0; i < 8; i++) {
      const uint4 v = lds128(a + (st == 3 ? i & 3 : i) * 2048);
      m = min(min(m, min(v.x, v.y)), min(v.z, v.w));
    }
    __syncwarp();
    if (lane == 0) mbar_arrive(bars + (B_REL1 + half * 4 + st) * 8);
  }
  pair_all(m, half);
}
__device__ __forceinline__ void proj_out(int layer, int rt, int cs, int half, __nv_bfloat16* out, uint32_t sb, int warp, int lane) {
  const uint32_t bars = sb + BARS, tbar = bars + (B_TP1 + half * 4) * 8, par = layer & 1;
  const uint32_t erel = bars + (B_REL1 + half * 4) * 8;
  const uint64_t dx = half << 11;
  const unsigned char* gsrc = (const unsigned char*)g_o + (size_t)rt * ACT_TILE_BYTES + warp * 256 + lane * 4;
  uint32_t xr[14];
  {
    const unsigned char* yp = (const unsigned char*)g_y + (size_t)(par * NTILE + rt) * ACT_TILE_BYTES + (7 * cs) * 1024 + warp * 256 + lane * 4;
#pragma unroll
    for (int i = 0; i < 14; i++) xr[i] = ld_relaxed((const unsigned*)(yp + (i >> 1) * 1024 + (i & 1) * 128));
  }
  float acc[28];
  uint32_t trdy = 0;
  mbar_wait(bars + B_W1RDY * 8, par);
#define OUT_MMA(ST)                                                                                   \
  if (!trdy) mbar_wait(tbar + ST * 8, par);                                                           \
  wg_fence();                                                                                         \
  _Pragma("unroll") for (int ks = 8 * ST; ks < (ST == 3 ? 28 : 8 * ST + 8); ks++) {                   \
    const uint64_t da = mkdesc(ks * 2048, 1024, 128) ^ dx, db = mkdesc(W1R + ks * 256, 128, W1_SBO);  \
    if (ks == 0) wgmma_p1<0>(acc, da, db); else wgmma_p1<1>(acc, da, db);                             \
  }                                                                                                   \
  wg_commit();                                                                                        \
  if (ST < 3) trdy = mbar_test(tbar + (ST + 1) * 8, par);                                             \
  if (ST > 0) {                                                                                       \
    wg_wait<1>();                                                                                     \
    if (lane == 0) mbar_arrive(erel + (ST > 0 ? ST - 1 : 0) * 8);                                     \
  }
  OUT_MMA(0) OUT_MMA(1) OUT_MMA(2) OUT_MMA(3)
#undef OUT_MMA
  wg_wait<0>();
  fence_regs(acc);
  if (lane == 0) mbar_arrive(erel + 24);
  uint32_t w[15];
  auto finish = [&]() {
#pragma unroll
    for (int i = 0; i < 14; i++) {
      acc[2 * i] += bf_lo(xr[i]);
      acc[2 * i + 1] += bf_hi(xr[i]);
    }
    pack_y(w, acc, lane);
  };
  finish();
  fence_regs(w);
  if (NEED_REDO(pair_all(1u, half))) {
    redo_rows<7, false>(acc, gsrc, 0u, 0u, 0, lane);
    finish();
    __syncwarp();
  }
  if (lane == 0) mbar_arrive(bars + B_W1FREE * 8);
  if (layer < NLAYERS - 1) {
    store_y(w, par ^ 1, rt, cs, warp, lane);
  } else {
    __nv_bfloat16* op = out + (size_t)(rt * 64 + warp * 16 + (lane >> 2)) * DM + cs * 56 + (lane & 3) * 2;
#pragma unroll
    for (int i = 0; i < 14; i++) stg32(op + (i & 1) * 8 * DM + (i >> 1) * 8, w[i]);
  }
}

__device__ __forceinline__ void qkv_main(float (&acc)[44], float (&rs)[2], int part, int nl, int rt, int half, uint32_t sb, int warp, int lane) {
  const uint32_t bars = sb + BARS, tbar = bars + (B_TP2 + half * 4) * 8, par = nl & 1;
  const uint32_t erel = bars + (B_REL2 + half * 4) * 8;
  const int c = lane & 3;
  const unsigned char* gsrc = (const unsigned char*)g_y + (size_t)(par * NTILE + rt) * ACT_TILE_BYTES + warp * 256 + lane * 4;
  const uint32_t la = sb + 4 * SLOT + (lane >> 4) * 1024 + (warp * 2 + ((lane >> 3) & 1)) * 128 + (lane & 7) * 16;
  const uint32_t lb = la - (2 - half) * 4 * SLOT;
  mbar_wait(bars + B_W2RDY * 8, par);
  mbar_wait(tbar, par);
  uint32_t x[2][4], a[2][2][4];
  load_frags<2>(x, la);
  uint32_t m2[2];
  float mean[2];
#pragma unroll
  for (int hh = 0; hh < 2; hh++) {
    const int row = warp * 16 + (lane >> 2) + 8 * hh;
    uint4 sv = lds128(sb + STATS + row * 64 + c * 16);
    if (missing(sv)) sv = repair((const unsigned char*)(g_stats + ((par * NTILE + rt) * 64 + row) * 8) + c * 16);
    mean[hh] = __uint_as_float(sv.x) + __uint_as_float(sv.z);
    rs[hh] = __uint_as_float(sv.y) + __uint_as_float(sv.w);
  }
  __syncwarp();
#pragma unroll
  for (int hh = 0; hh < 2; hh++) {
    mean[hh] = quad_sum(mean[hh]) * (1.f / DM);
    m2[hh] = pack_bf16(mean[hh], mean[hh]);
  }
  if (half == 1) {
    mbar_wait(bars + B_WFREE * 8, par);
    __nanosleep(300);
  }
  uint32_t chk = 0xffffffffu, trdy = 0, wrdy = 0;
  const uint64_t dpart = part * (10 * W2_SBO >> 4);
#pragma unroll
  for (int g = 0; g < 14; g++) {
    chk = min_frags<2>(chk, x);
    if ((g & 1) == 0 && g > 0 && !wrdy) mbar_wait(bars + (B_W2RDY + (g >> 1)) * 8, par);
    if (g >= 2) wg_wait<1>();
#pragma unroll
    for (int i = 0; i < 8; i++) a[g & 1][i >> 2][i & 3] = sub_bf16x2(x[i >> 2][i & 3], m2[i & 1]);
    fence_regs(a[g & 1][0]);
    fence_regs(a[g & 1][1]);
    wg_fence();
#pragma unroll
    for (int i = 0; i < 2; i++) {
      const uint64_t db = mkdesc(w2_chunk_off(g >> 1) + ((g & 1) * 2 + i) * 256, 128, W2_SBO) + dpart;
      const uint32_t(&f)[4] = a[g & 1][i];
      if (g == 0 && i == 0) wgmma_p2<0>(acc, f[0], f[1], f[2], f[3], db); else wgmma_p2<1>(acc, f[0], f[1], f[2], f[3], db);
    }
    wg_commit();
    if (((g & 3) == 3 || g == 13) && lane == 0) mbar_arrive(erel + (g >> 2) * 8);
    if (g < 13) {
      if ((g & 3) == 3 && !trdy) mbar_wait(tbar + ((g + 1) >> 2) * 8, par);
      load_frags<2>(x, (g + 1 < 8 ? la : lb) + (g + 1) * 4096);
      if ((g & 3) == 1) trdy = mbar_test(tbar + ((g + 3) >> 2) * 8, par);
      if ((g & 1) == 0 && g < 12) wrdy = mbar_test(bars + (B_W2RDY + (g >> 1) + 1) * 8, par);
    }
  }
#pragma unroll
  for (int hh = 0; hh < 2; hh++) rs[hh] = rsqrtf(fmaxf(quad_sum(rs[hh]) * (1.f / DM) - mean[hh] * mean[hh], 0.f) + 1e-5f);
  wg_wait<0>();
  fence_regs(acc);
  if (NEED_REDO(chk)) redo_rows<11, true>(acc, gsrc, m2[0], m2[1], part * 10 * W2_SBO, lane);
  __syncwarp();
  if (lane == 0) mbar_arrive(bars + (B_WFREE + half) * 8);
}
template <int PART>
__device__ __forceinline__ void qkv_store(const float (&acc)[44], const float (&rs)[2], int nl, unsigned ep4, int rt, int cs, int half, int warp, int lane) {
  const int par = nl & 1, c = lane & 3;
  const float qs = 0.18898223650461362f * 1.4426950408889634f;
  const size_t hb = (size_t)(par * NH + 2 * cs) * NTILE + rt;
  unsigned char* fp = (PART == 0 ? (unsigned char*)g_q + hb * 4096 + warp * 1024
                                 : (unsigned char*)g_kv + hb * 8192 + 4096 + (warp >> 1) * 2048 + (warp & 1) * 256) + lane * 4;
  constexpr int FR = PART == 0 ? 512 : 128, FD = PART == 0 ? 128 : 512;
  constexpr size_t hstride = (size_t)NTILE * (PART == 0 ? 4096 : 8192);
  unsigned char* kp = (unsigned char*)g_kv + (hb + PART * NTILE) * 8192 + warp * 1024 + lane * 4;
  const uint32_t jm = (rt & 1) ? JM1 : JM0;
  const bool lo2 = c < 2, first = (c & 1) == 0;
#pragma unroll
  for (int hh = 0; hh < 2; hh++) {
    const float sc = PART == 0 ? rs[hh] * qs : rs[hh];
    const uint32_t pad = PART == 0 ? (first ? 0xC25C4340u   : 0x00003BAFu  ) : (first ? 0x00003F80u : 0x8000u);
#pragma unroll
    for (int jj = 0; jj < 7; jj++) {
      const int jl = PART == 0 ? jj : 4 + jj;
      const uint32_t v = pack_bf16(acc[4 * jl + 2 * hh] * sc, acc[4 * jl + 2 * hh + 1] * sc);
      auto st = [&](unsigned char* a, uint32_t w) { st_word(a, w); };
      if (jj < 3) st(fp + hh * FR + jj * FD, v);
      else if (jj > 3) st(fp + hstride + hh * FR + (jj - 4) * FD, v);
      else {
        st(fp + hh * FR + 3 * FD, lo2 ? v : pad);
        st(fp + hstride + hh * FR + 3 * FD, lo2 ? pad : v);
      }
    }
  }
  float nk[2] = {0.f, 0.f};
#pragma unroll
  for (int hh = 0; hh < 2; hh++) {
    const bool poly = (jm >> (warp * 2 + hh)) & 1;
    const uint32_t kpad = first ? (poly ? 0x00003F80u : 0x3F800000u) : (poly ? 0x00003F80u : 0x8000u);
#pragma unroll
    for (int j = 0; j < 4; j++) {
      const int jl = PART == 0 ? 7 + j : (j + 1) & 3;
      const float v0 = acc[4 * jl + 2 * hh] * rs[hh], v1 = acc[4 * jl + 2 * hh + 1] * rs[hh];
      const bool real = j < 3 || (PART == 0 ? lo2 : !lo2);
      nk[hh] += real ? v0 * v0 + v1 * v1 : 0.f;
      st_word(kp + hh * 512 + j * 128, real ? pack_bf16(v0, v1) : kpad);
    }
  }
  float km = fmaxf(quad_sum(nk[0]), quad_sum(nk[1]));
#pragma unroll
  for (int d = 4; d < 32; d <<= 1) km = fmaxf(km, __shfl_xor_sync(0xffffffffu, km, d));
  if (lane == 0) atomicMax(&g_kmax[(par * NH + 2 * cs + PART) * 16], ((unsigned long long)(ep4 + nl + 1) << 32) | __float_as_uint(km));
  hand_over<256>(5 + half);
}

__device__ __forceinline__ void tile_w2(const __nv_bfloat16* w, int set, int kb, int cs, int t) {
#pragma unroll
  for (int i = 0; i < 3; i++) {
    const int idx = t + i * 256;
    if (idx < 588) {
      const int k = kb * 28 + idx / 21, g = idx % 21;
      const uint4 v = __ldg((const uint4*)(w + (size_t)k * (3 * DM) + (g / 7) * DM + cs * 56 + (g % 7) * 8));
      *(uint4*)((unsigned char*)g_w2 + (size_t)(set * 8 + cs) * W2_IMG + (k >> 6) * W2_CHUNK + g * W2_SBO + (k & 63) * 16) = v;
    }
  }
}
__device__ __forceinline__ void tile_w1(const __nv_bfloat16* w, int set, int kb, int cs, int t) {
  if (t < 196) {
    const int k = kb * 28 + t / 7, g = t % 7;
    const uint4 v = __ldg((const uint4*)(w + (size_t)k * DM + cs * 56 + g * 8));
    *(uint4*)((unsigned char*)g_w1 + (size_t)(set * 8 + cs) * W1_IMG + g * W1_SBO + k * 16) = v;
  }
}

__device__ __forceinline__ void put_w2(uint32_t sb, int set, int cs, int ch) {
  const uint32_t bar = sb + BARS + (B_W2RDY + ch) * 8;
  mbar_expect_tx(bar, W2_CHUNK);
  bulk_g2s(sb + w2_chunk_off(ch), (const unsigned char*)g_w2 + (size_t)(set * 8 + cs) * W2_IMG + ch * W2_CHUNK, W2_CHUNK, bar);
}

__global__ void __launch_bounds__(NTHREADS, 1)
mha_stack_kernel(const __nv_bfloat16* __restrict__ x, const __nv_bfloat16* __restrict__ wqkvA, const __nv_bfloat16* __restrict__ woA,
                 const __nv_bfloat16* __restrict__ wqkvB, const __nv_bfloat16* __restrict__ woB, __nv_bfloat16* __restrict__ out, uint64_t dbase) {
  extern __shared__ __align__(1024) unsigned char smem[];
  constexpr uint32_t sb = SM_BASE, bars = sb + BARS;
  const int tid = threadIdx.x, wg = (tid >> 7) - 1, warp = (tid >> 5) & 3, lane = tid & 31;
  const int hi = blockIdx.x >> 3, lo = blockIdx.x & 7;
  if (tid == 0) {
    if ((uint32_t)__cvta_generic_to_shared(smem) != SM_BASE) __trap();
    for (int i = 0; i < 8; i++) mbar_init(bars + (B_FULLKV + i) * 8, 1);
    for (int i = 0; i < 16; i++) mbar_init(bars + (B_EKV + i) * 8, 16);
    for (int i = 0; i < 2; i++) mbar_init(bars + (B_WFREE + i) * 8, 8);
    for (int i = 0; i < 16; i++) { mbar_init(bars + (B_REL1 + i) * 8, 8); mbar_init(bars + (B_TP1 + i) * 8, 1); }
    mbar_init(bars + B_TKV0 * 8, 1);
    asm volatile("st.shared.u32 [%0], 0;" ::"r"(sb + KBAD) : "memory");
    mbar_init(bars + B_W1RDY * 8, 1);
    for (int i = 0; i < 7; i++) mbar_init(bars + (B_W2RDY + i) * 8, 1);
    mbar_init(bars + B_W1FREE * 8, 8);
    mbar_init(bars + B_ZOK * 8, 1);
    asm volatile("fence.mbarrier_init.release.cluster;" ::: "memory");
  }
  const unsigned ep = *(volatile unsigned*)&g_epoch, ep4 = NLAYERS * ep;
  __syncthreads();

  if (wg < 0) {
    if (warp < 2) {
      const int hf = warp, rt = hf * 16 + hi;
      const bool issuer = lane == 0;
      publish<128>(1 + hf, &g_flagY[rt * 32], lane);
      __syncwarp();
      auto put = [&](uint32_t ebar, uint32_t epar, uint32_t tbar, uint32_t dst, const unsigned char* src, uint32_t bytes) {
        mbar_wait(ebar, epar);
        if (issuer) {
          mbar_expect_tx(tbar, bytes);
          bulk_g2s(dst, src, bytes, tbar);
        }
      };
#pragma unroll 1
      for (int l = 0; l < NLAYERS; l++) {
        const int par = l & 1;
        {
          const uint32_t tb = bars + (B_TP2 + hf * 4) * 8;
          const unsigned char* src = (const unsigned char*)g_y + (size_t)(par * NTILE + rt) * ACT_TILE_BYTES;
          const bool first = l == 0 && hf == 0 && issuer;
          if (issuer) {
#pragma unroll
            for (int st = 0; st < 4; st++) mbar_expect_tx(tb + st * 8, st == 0 ? 4096 + 16384 : st == 3 ? 8192 : 16384);
          }
          if (l == 0) {
            wait_flag(&g_flagY[rt * 32], 8u * (ep + 1));
            if (hf == 0) wait_flag(&g_flagW[lo * 32], 16u * (ep + 1));
            fence_proxy_async();
          } else {
            wait_canary(g_stats + ((par * NTILE + rt) * 64 + (lane >> 3) * 16 + 15) * 8 + (lane & 7), 4);
          }
#pragma unroll
          for (int st = 0; st < 4; st++) {
            mbar_wait(bars + (hf == 0 ? B_REL1 + 4 + st : st < 2 ? B_REL2 + st : B_REL2 + 2 + st) * 8, par ^ hf ^ 1);
            if (issuer) {
              if (st == 0) bulk_g2s(sb + STATS, g_stats + (par * NTILE + rt) * 512, 4096, tb);
              bulk_g2s(sb + 2 * (st < 2 ? st + 2 : st - 2 + 2 * hf) * SLOT, src + 2 * st * 8192, st == 3 ? 8192 : 16384, tb + st * 8);
            }
            if (first) { put_w2(sb, 0, lo, 2 * st); if (st < 3) put_w2(sb, 0, lo, 2 * st + 1); }
          }
        }
        if (hf == 0) {
          const unsigned char* kv = (const unsigned char*)g_kv + (size_t)(par * NH + hi) * NTILE * 8192;
          const unsigned* fq = &g_flagQ[(hi >> 1) * 32];
          const unsigned tq = ep4 + l + 1;
          if (issuer) mbar_expect_tx(bars + B_TKV0 * 8, 32768);
          mbar_wait(bars + (B_REL2 + 2) * 8, par);
          mbar_wait(bars + (B_REL2 + 3) * 8, par);
          if (l == 0) wait_flag4(fq, tq);
          else wait_canary(kv + (lane >> 3) * 8192 + ((lane & 1) ? 4096 + ((lane >> 2) & 1) * 2048 + 1536 + (lane & 2) * 128 + 252 : ((lane >> 1) & 3) * 1024 + 1020), 0);
          if (issuer) {
            bulk_g2s(sb, kv, 16384, bars + B_TKV0 * 8);
            bulk_g2s(sb + 2 * SLOT, kv + 16384, 16384, bars + B_TKV0 * 8);
          }
          wait_flag4(fq + 4, tq);
          put(bars + (B_REL2 + 6) * 8, par, bars + (B_FULLKV + 2) * 8, sb + 4 * SLOT, kv + 32768, 16384);
          put(bars + (B_REL2 + 7) * 8, par, bars + (B_FULLKV + 3) * 8, sb + 6 * SLOT, kv + 49152, 16384);
          mbar_wait(bars + B_WFREE * 8, par);
          mbar_wait(bars + (B_WFREE + 1) * 8, par);
#pragma unroll 1
          for (int st = 4; st < 16; st++) {
            const int j = st * 2;
            if ((st & 1) == 0) wait_flag4(fq + j, tq);
            if (st == 14) {
              wait_flag4(fq, tq);
              const uint32_t km = ldcg32(&g_kmax[(par * NH + hi) * 16]);
              if (issuer) asm volatile("st.shared.u32 [%0], %1;" ::"r"(sb + KMAX + par * 4), "r"(km) : "memory");
            }
            if (st >= 8) mbar_wait(bars + (B_EKV + st - 8) * 8, par);
            if (issuer) {
              mbar_expect_tx(bars + (B_FULLKV + (st & 7)) * 8, 16384);
              bulk_g2s(sb + 2 * (st & 7) * SLOT, kv + (size_t)j * 8192, 16384, bars + (B_FULLKV + (st & 7)) * 8);
            }
            if (st == 9) {
              if (l == 0) { wait_flag(&g_flagW[(8 + lo) * 32], 16u * (ep + 1)); fence_proxy_async(); }
              if (issuer) {
                mbar_expect_tx(bars + B_W1RDY * 8, W1_IMG);
                bulk_g2s(sb + W1R, (const unsigned char*)g_w1 + (size_t)(par * 8 + lo) * W1_IMG, W1_IMG, bars + B_W1RDY * 8);
              }
            }
            if ((st == 11 || st == 13) && l < NLAYERS - 1 && issuer) put_w2(sb, par ^ 1, lo, (st - 5) >> 1);
          }
        } else if (l < NLAYERS - 1) {
          if (l == 0) { wait_flag(&g_flagW[(8 + lo) * 32], 16u * (ep + 1)); fence_proxy_async(); }
          mbar_wait(bars + (B_EKV3 + 4) * 8, par);
#pragma unroll 1
          for (int ch = 0; ch < 3; ch++) {
            mbar_wait(bars + (B_EKV3 + 5 + ch) * 8, par);
            if (issuer) put_w2(sb, par ^ 1, lo, ch);
          }
        }
        {
          const unsigned char* src = (const unsigned char*)g_o + (size_t)rt * ACT_TILE_BYTES;
          const uint32_t tb = bars + (B_TP1 + hf * 4) * 8;
          if (issuer) {
#pragma unroll
            for (int st = 0; st < 4; st++) mbar_expect_tx(tb + st * 8, st == 3 ? 8192 : 16384);
          }
          mbar_wait(bars + B_ZOK * 8, par);
          if (hf == 0) {
#pragma unroll 1
            for (int st = 0; st < 4; st++) mbar_wait(bars + (B_EKV3 + st) * 8, par);
          }
          const unsigned char* cn = src + (7 * ((lane & 15) >> 1) + 3) * 1024 + ((lane >> 4) * 16 + 15) * 16 + (lane & 1) * 8;
          uint32_t seen = 0;
#pragma unroll
          for (int st = 0; st < 4; st++) {
            wait_canary_lanes(cn, 512, st == 0 ? 0x001F001Fu : st == 1 ? 0x03F003F0u : st == 2 ? 0x3E003E00u : 0xE000E000u, seen);
            if (hf == 1) mbar_wait(bars + (B_REL1 + ((st + 2) & 3)) * 8, par);
            if (issuer) bulk_g2s(sb + 2 * ((st + 2 * hf) & 3) * SLOT, src + 2 * st * 8192, st == 3 ? 8192 : 16384, tb + st * 8);
          }
        }
        if (hf == 1 && l < NLAYERS - 1) {
          mbar_wait(bars + B_W1FREE * 8, par);
          if (issuer) {
            put_w2(sb, par ^ 1, lo, 5);
            put_w2(sb, par ^ 1, lo, 6);
          }
        }
      }
    } else {
      {
        const int hf = warp - 2;
        const uint4 z4 = make_uint4(0, 0, 0, 0);
        if (hf == 0) publish<256>(3, &g_flagW[lo * 32], lane);
        if (hf == 1) publish<256>(4, &g_flagW[(8 + lo) * 32], lane);
#pragma unroll 1
        for (int l = 0; l < NLAYERS; l++) {
          publish<256>(5 + hf, &g_flagQ[lo * 32 + hf * 16 + hi], lane);
          wait_flag(&g_flagQ[lo * 32 + lane], ep4 + l + 1);
          __syncwarp();
#pragma unroll
          for (int m = 0; m < 2; m++) {
            unsigned char* op = (unsigned char*)g_o + (size_t)(hf * 16 + lo * 2 + m) * ACT_TILE_BYTES + 7 * (hi >> 1) * 1024;
#pragma unroll
            for (int i = 0; i < 6; i++) *(uint4*)(op + (hi & 1) * 4096 + i * 512 + lane * 16) = z4;
#pragma unroll
            for (int i = 0; i < 2; i++) *(uint2*)(op + 3072 + (i * 32 + lane) * 16 + (hi & 1) * 8) = make_uint2(0, 0);
          }
          if (l < NLAYERS - 1) {
            const int np = (l & 1) ^ 1, rt = hf * 16 + hi;
            unsigned char* yp = (unsigned char*)g_y + (size_t)(np * NTILE + rt) * ACT_TILE_BYTES + lo * 7168 + lane * 16;
#pragma unroll
            for (int i = 0; i < 14; i++) *(uint4*)(yp + i * 512) = z4;
#pragma unroll
            for (int i = 0; i < 2; i++) g_stats[((np * NTILE + rt) * 64 + i * 32 + lane) * 8 + lo] = make_float2(0.f, 0.f);
#pragma unroll
            for (int e = 0; e < 2; e++) {
              const size_t hb = (size_t)(np * NH + 2 * lo + e) * NTILE;
#pragma unroll
              for (int i = 0; i < 8; i++) g_q[(hb + rt) * 256 + i * 32 + lane] = z4;
            }
            if (hi < 4) {
              const size_t hb = (size_t)(np * NH + 2 * lo + hf) * NTILE + hi;
#pragma unroll
              for (int i = 0; i < 16; i++) g_kv[hb * 512 + i * 32 + lane] = z4;
            }
          }
          __syncwarp();
          if (l == 1 && hf == 1 && lane == 0 && blockIdx.x == 0) *(volatile unsigned*)&g_epoch = ep + 1;
          if (lane == 0) red_release(&g_zcount);
          if (hf == 0) {
            __syncwarp();
            wait_flag(&g_zcount, 2u * NCTA * (ep4 + l + 1));
            if (lane == 0) mbar_arrive(bars + B_ZOK * 8);
          }
        }
      }
    }
  } else {
    const int half = wg >> 1;
    const int prt = half * 16 + hi;
    const int art = half * 16 + lo * 2 + (wg & 1);
    if ((wg & 1) == 0) {
      const __nv_bfloat16* xp = x + (size_t)(prt * 64 + warp * 16 + (lane >> 2)) * DM + lo * 56 + (lane & 3) * 2;
      float y[28];
#pragma unroll
      for (int j = 0; j < 7; j++) {
        const uint32_t a = *(const uint32_t*)(xp + j * 8), b = *(const uint32_t*)(xp + 8 * DM + j * 8);
        y[4 * j] = bf_lo(a); y[4 * j + 1] = bf_hi(a); y[4 * j + 2] = bf_lo(b); y[4 * j + 3] = bf_hi(b);
      }
      uint32_t w[15];
      pack_y(w, y, lane);
      store_y(w, 0, prt, lo, warp, lane);
      hand_over<128>(1 + half);
    } else {
      const int t = half * 128 + (tid & 127);
      tile_w2(wqkvA, 0, hi, lo, t);
      hand_over<256>(3);
    }
    if (half == 1) {
      tile_w1(woA, 0, hi, lo, tid - 384);
      tile_w2(wqkvB, 1, hi, lo, tid - 384);
      tile_w1(woB, 1, hi, lo, tid - 384);
      hand_over<256>(4);
    }
#pragma unroll 1
    for (int l = 0; l < NLAYERS; l++) {
      {
        float acc[44], rs[2];
        qkv_main(acc, rs, wg & 1, l, prt, half, sb, warp, lane);
        if ((wg & 1) == 0) qkv_store<0>(acc, rs, l, ep4, prt, lo, half, warp, lane);
        else qkv_store<1>(acc, rs, l, ep4, prt, lo, half, warp, lane);
      }
      attention(l, hi, art, wg, ep4, sb, warp, lane, dbase);
      if ((wg & 1) == 0) proj_out(l, prt, lo, half, out, sb, warp, lane);
      else proj_out_check(l, half, sb, lane);
    }
  }
}

}

extern "C" void kernel_launch(void* const* d_in, const int* in_sizes, int n_in, void* d_out, int out_size) {
  (void)in_sizes; (void)n_in; (void)out_size;
  static bool configured = false;
  if (!configured) {
    cudaFuncSetAttribute(mk::mha_stack_kernel, cudaFuncAttributeMaxDynamicSharedMemorySize, mk::SMEM_BYTES);
    configured = true;
  }
  mk::mha_stack_kernel<<<mk::NCTA, mk::NTHREADS, mk::SMEM_BYTES>>>(
      (const __nv_bfloat16*)d_in[0], (const __nv_bfloat16*)d_in[1], (const __nv_bfloat16*)d_in[2],
      (const __nv_bfloat16*)d_in[4], (const __nv_bfloat16*)d_in[5], (__nv_bfloat16*)d_out, mk::mkdesc(0, 128, 512));
}
```
